```python
import torch

def _softmax(x, axis=-1):
    return torch.softmax(x, dim=axis)
def _gelu(x):
    return torch.nn.functional.gelu(x, approximate="tanh")
def _silu(x):
    return torch.nn.functional.silu(x)
def _sigmoid(x):
    return torch.sigmoid(x)
def _layernorm(x, axis=-1, eps=1e-5):
    m = x.mean(dim=axis, keepdim=True)
    v = x.var(dim=axis, keepdim=True, unbiased=False)
    return (x - m) / torch.sqrt(v + eps)
def _scatter_add(tgt, idx, src, axis=0):
    return tgt.clone().index_add_(axis, idx, src)
def _segment_sum(src, seg, n):
    out = torch.zeros((n,) + src.shape[1:], dtype=src.dtype)
    return out.index_add_(0, seg, src)
def _pad(x, pw):
    flat = tuple(v for pair in reversed(pw) for v in pair)
    return torch.nn.functional.pad(x, flat)

kernel_name = 'gated_mix__gqa_block_cached__glu_gated_reglu__decode'

def setup_inputs():

    _w = (lambda a: (lambda t: t.to(torch.bfloat16) if t.is_floating_point() else t)(torch.as_tensor(a)))
    def _A_setup():
        B, Sq, D = 4, 1, 512
        Hq, Hkv, Sk, Dh = 32, 8, 16384, 128
        assert Hq % Hkv == 0, (Hq, Hkv)
        return {
            "x": _w((lambda *s: torch.randn(*s, dtype=torch.bfloat16) * 0.05)(B, Sq, D)),
            "k_cache": _w((lambda *s: torch.randn(*s, dtype=torch.bfloat16) * 3.2)(B, Hkv, Sk, Dh)),
            "v_cache": _w((lambda *s: torch.randn(*s, dtype=torch.bfloat16) * 0.2)(B, Hkv, Sk, Dh)),
            "wq": _w((lambda *s: torch.randn(*s, dtype=torch.bfloat16) * 3.2)(D, Hq * Dh) * (D ** -0.5)),
            "wo": _w((lambda *s: torch.randn(*s, dtype=torch.bfloat16) * 0.2)(Hq * Dh, D) * ((Hq * Dh) ** -0.5)),
        }
    _A_in = _A_setup()

    def _B_setup():
        B, S, D, F = 4, 1, 512, 1792
        return {
            "x": _w((lambda *s: torch.randn(*s, dtype=torch.bfloat16) * 0.05)(B, S, D)),
            "W_gate": _w((lambda *s: torch.randn(*s, dtype=torch.bfloat16) * 0.4)(D, F) * (2.0 / D) ** 0.5),
            "W_up": _w((lambda *s: torch.randn(*s, dtype=torch.bfloat16) * 0.4)(D, F) * (2.0 / D) ** 0.5),
            "W_down": _w((lambda *s: torch.randn(*s, dtype=torch.bfloat16) * 0.4)(F, D) * (1.0 / F) ** 0.5),
        }
    _B_in = _B_setup()

    return {
        "A_x": _A_in["x"],
        "A_k_cache": _A_in["k_cache"],
        "A_v_cache": _A_in["v_cache"],
        "A_wq": _A_in["wq"],
        "A_wo": _A_in["wo"],
        "B_x": _B_in["x"],
        "B_W_gate": _B_in["W_gate"],
        "B_W_up": _B_in["W_up"],
        "B_W_down": _B_in["W_down"],
        "gate_w": _w((lambda *s: torch.randn(*s, dtype=torch.bfloat16) * 0.05)(512) * 16.0),
    }

def reference(A_x, A_k_cache, A_v_cache, A_wq, A_wo, B_x, B_W_gate, B_W_up, B_W_down, gate_w):
    def _A_ref(x, k_cache, v_cache, wq, wo):
        B, Sq, D = x.shape
        Hq, Dh = 32, 128
        Hkv = k_cache.shape[1]
        rep = Hq // Hkv
        q = (lambda x, *d: x.permute(*d))((x @ wq).reshape(B, Sq, Hq, Dh), 0, 2, 1, 3)
        k = (lambda x, n, axis: torch.repeat_interleave(x, n, dim=axis))(k_cache, rep, axis=1)
        v = (lambda x, n, axis: torch.repeat_interleave(x, n, dim=axis))(v_cache, rep, axis=1)
        scores = torch.einsum("bhqd,bhkd->bhqk", q, k) * (Dh ** -0.5)
        p = _softmax(scores, axis=-1)
        o = torch.einsum("bhqk,bhkd->bhqd", p, v)
        return (lambda x, *d: x.permute(*d))(o, 0, 2, 1, 3).reshape(B, Sq, Hq * Dh) @ wo

    def _B_ref(x, W_gate, W_up, W_down):
        gate = torch.einsum("bsd,df->bsf", x, W_gate)
        up = torch.einsum("bsd,df->bsf", x, W_up)
        gate = gate * (lambda x, dt: x.to(dt))(gate > 0, gate.dtype)
        h = gate * up
        return torch.einsum("bsf,fd->bsd", h, W_down)

    x = A_x
    g = _sigmoid((x * gate_w).sum(-1, keepdims=True))
    a = _A_ref(x, A_k_cache, A_v_cache, A_wq, A_wo)
    b = _B_ref(x, B_W_gate, B_W_up, B_W_down)
    return g * a + (1 - g) * b
```

```cpp
#include <cuda_runtime.h>
#include <cuda_bf16.h>
#include <cuda.h>
#include <stdint.h>

namespace {

constexpr int NCTA        = 128;
constexpr int NTHREADS    = 160;
constexpr int STAGE_BYTES = 32768;
#define NSTAGES 6
#define WINDOW 2
static_assert(WINDOW < NSTAGES, "window must be smaller than the ring");
constexpr int TILE   = 128;
constexpr int NTILES = 4096 / TILE;
constexpr int NFFN   = 112;

constexpr int OFF_BAR = NSTAGES * STAGE_BYTES;
constexpr int OFF_XS  = OFF_BAR + 256;
constexpr int XS_STRIDE = 1040;
constexpr int OFF_QS  = OFF_XS + 4 * XS_STRIDE;
constexpr int QS_STRIDE = 272;
constexpr int OFF_OS  = OFF_QS + 4 * QS_STRIDE;
constexpr int OFF_HS  = OFF_OS + 4 * QS_STRIDE;
constexpr int HS_STRIDE = 144;
constexpr int OFF_SO  = OFF_HS + 4 * HS_STRIDE;
constexpr int SO_STRIDE = 136;
constexpr int OFF_SM  = OFF_SO + 16 * SO_STRIDE * 4;
constexpr int OFF_GS  = OFF_SM + 128;
constexpr int OFF_UP  = OFF_GS + 32;
constexpr int SMEM_USED  = OFF_UP + 256;
constexpr int SMEM_BYTES = SMEM_USED + 1024;

__device__ uint32_t g_epoch[NCTA];
__device__ __align__(128) uint32_t g_q[4 * 4096];
__device__ __align__(128) uint32_t g_h[4 * 1792];
__device__ __align__(128) uint32_t g_part[4 * 32 * 4 * 128];
__device__ __align__(128) unsigned long long g_ml[4 * 32 * 4 * 2];
__device__ __align__(128) uint32_t g_y[4 * 32 * 32 * 16];

#define PROFW(w, i)
#define PROF(i)
#define PROFP(i)

constexpr int SPIN_LIMIT = 1 << 22;
#define SPIN_FAIL(code) __trap()

__device__ __forceinline__ uint32_t smem_u32(const void* p) { return (uint32_t)__cvta_generic_to_shared(p); }
__device__ __forceinline__ void mbar_init(uint32_t bar, uint32_t cnt) {
    asm volatile("mbarrier.init.shared::cta.b64 [%0], %1;" :: "r"(bar), "r"(cnt) : "memory");
}
__device__ __forceinline__ void mbar_expect_tx(uint32_t bar, uint32_t bytes) {
    asm volatile("mbarrier.arrive.expect_tx.shared::cta.b64 _, [%0], %1;" :: "r"(bar), "r"(bytes) : "memory");
}
__device__ __forceinline__ void mbar_arrive(uint32_t bar) {
    asm volatile("mbarrier.arrive.shared::cta.b64 _, [%0];" :: "r"(bar) : "memory");
}
__device__ __forceinline__ bool mbar_try_wait(uint32_t bar, uint32_t parity) {
    uint32_t ok;
    asm volatile("{\n.reg .pred p;\nmbarrier.try_wait.parity.shared::cta.b64 p, [%1], %2;\nselp.u32 %0, 1, 0, p;\n}"
                 : "=r"(ok) : "r"(bar), "r"(parity) : "memory");
    return ok;
}
__device__ __forceinline__ void mbar_wait(uint32_t bar, uint32_t parity, int code = 0) {
    int it = 0;
    while (!mbar_try_wait(bar, parity)) { if (++it > SPIN_LIMIT) SPIN_FAIL(code); }
}
__device__ __forceinline__ void bulk_load(uint32_t dst, const void* src, uint32_t bytes, uint32_t bar) {
    asm volatile("cp.async.bulk.shared::cluster.global.mbarrier::complete_tx::bytes [%0], [%1], %2, [%3];"
                 :: "r"(dst), "l"(src), "r"(bytes), "r"(bar) : "memory");
}
__device__ __forceinline__ void tma2d(uint32_t dst, const CUtensorMap* tm, int c0, int c1, uint32_t bar) {
    asm volatile("cp.async.bulk.tensor.2d.shared::cluster.global.mbarrier::complete_tx::bytes [%0], [%1, {%3, %4}], [%2];"
                 :: "r"(dst), "l"(tm), "r"(bar), "r"(c0), "r"(c1) : "memory");
}
__device__ __forceinline__ void tma3d(uint32_t dst, const CUtensorMap* tm, int c0, int c1, int c2, uint32_t bar) {
    asm volatile("cp.async.bulk.tensor.3d.shared::cluster.global.mbarrier::complete_tx::bytes [%0], [%1, {%3, %4, %5}], [%2];"
                 :: "r"(dst), "l"(tm), "r"(bar), "r"(c0), "r"(c1), "r"(c2) : "memory");
}
__device__ __forceinline__ void prefetch_map(const CUtensorMap* tm) {
    asm volatile("prefetch.tensormap [%0];" :: "l"(tm) : "memory");
}
__device__ __forceinline__ void ldsm4(uint32_t (&r)[4], uint32_t addr) {
    asm volatile("ldmatrix.sync.aligned.m8n8.x4.shared.b16 {%0,%1,%2,%3}, [%4];"
                 : "=r"(r[0]), "=r"(r[1]), "=r"(r[2]), "=r"(r[3]) : "r"(addr) : "memory");
}
__device__ __forceinline__ void ldsm4t(uint32_t (&r)[4], uint32_t addr) {
    asm volatile("ldmatrix.sync.aligned.m8n8.x4.trans.shared.b16 {%0,%1,%2,%3}, [%4];"
                 : "=r"(r[0]), "=r"(r[1]), "=r"(r[2]), "=r"(r[3]) : "r"(addr) : "memory");
}
__device__ __forceinline__ void mma16816(float (&d)[4], const uint32_t (&a)[4], uint32_t b0, uint32_t b1) {
    asm volatile("mma.sync.aligned.m16n8k16.row.col.f32.bf16.bf16.f32 {%0,%1,%2,%3}, {%4,%5,%6,%7}, {%8,%9}, {%0,%1,%2,%3};"
                 : "+f"(d[0]), "+f"(d[1]), "+f"(d[2]), "+f"(d[3])
                 : "r"(a[0]), "r"(a[1]), "r"(a[2]), "r"(a[3]), "r"(b0), "r"(b1));
}
__device__ __forceinline__ uint32_t movm_t(uint32_t a) {
    uint32_t d;
    asm volatile("movmatrix.sync.aligned.m8n8.trans.b16 %0, %1;" : "=r"(d) : "r"(a));
    return d;
}
__device__ __forceinline__ uint32_t pack_bf16(float lo, float hi) {
    uint32_t d;
    asm("cvt.rn.bf16x2.f32 %0, %1, %2;" : "=r"(d) : "f"(hi), "f"(lo));
    return d;
}
__device__ __forceinline__ float ex2(float x) {
    float y;
    asm("ex2.approx.ftz.f32 %0, %1;" : "=f"(y) : "f"(x));
    return y;
}
__device__ __forceinline__ float bf16r(float x) { return __bfloat162float(__float2bfloat16_rn(x)); }
__device__ __forceinline__ uint32_t bf16bits(float x) { return (uint32_t)__bfloat16_as_ushort(__float2bfloat16_rn(x)); }
__device__ __forceinline__ void bar_sync(int id, int n) { asm volatile("bar.sync %0, %1;" :: "r"(id), "r"(n) : "memory"); }

__device__ __forceinline__ uint4 ldg_rlx4(const uint32_t* p) {
    uint4 v;
    asm volatile("ld.relaxed.gpu.global.v4.u32 {%0,%1,%2,%3}, [%4];" : "=r"(v.x), "=r"(v.y), "=r"(v.z), "=r"(v.w) : "l"(p) : "memory");
    return v;
}
__device__ __forceinline__ ulonglong2 ldg_rlx2x64(const unsigned long long* p) {
    ulonglong2 v;
    asm volatile("ld.relaxed.gpu.global.v2.u64 {%0,%1}, [%2];" : "=l"(v.x), "=l"(v.y) : "l"(p) : "memory");
    return v;
}
__device__ __forceinline__ void stg_rlx(uint32_t* p, uint32_t v) {
    asm volatile("st.relaxed.gpu.global.u32 [%0], %1;" :: "l"(p), "r"(v) : "memory");
}
__device__ __forceinline__ void stg_rlx4(uint32_t* p, uint32_t a, uint32_t b, uint32_t c, uint32_t d) {
    asm volatile("st.relaxed.gpu.global.v4.u32 [%0], {%1,%2,%3,%4};" :: "l"(p), "r"(a), "r"(b), "r"(c), "r"(d) : "memory");
}
__device__ __forceinline__ void stg_rlx2x64(unsigned long long* p, unsigned long long a, unsigned long long b) {
    asm volatile("st.relaxed.gpu.global.v2.u64 [%0], {%1,%2};" :: "l"(p), "l"(a), "l"(b) : "memory");
}
__device__ __forceinline__ float lds_f32(uint32_t a) { float v; asm volatile("ld.shared.f32 %0, [%1];" : "=f"(v) : "r"(a) : "memory"); return v; }
__device__ __forceinline__ float4 lds_f32x4(uint32_t a) {
    float4 v; asm volatile("ld.shared.v4.f32 {%0,%1,%2,%3}, [%4];" : "=f"(v.x), "=f"(v.y), "=f"(v.z), "=f"(v.w) : "r"(a) : "memory"); return v;
}
__device__ __forceinline__ uint4 lds_u32x4(uint32_t a) {
    uint4 v; asm volatile("ld.shared.v4.u32 {%0,%1,%2,%3}, [%4];" : "=r"(v.x), "=r"(v.y), "=r"(v.z), "=r"(v.w) : "r"(a) : "memory"); return v;
}
__device__ __forceinline__ void sts_f32(uint32_t a, float v) { asm volatile("st.shared.f32 [%0], %1;" :: "r"(a), "f"(v) : "memory"); }
__device__ __forceinline__ void sts_u32x2(uint32_t a, uint32_t x, uint32_t y) { asm volatile("st.shared.v2.u32 [%0], {%1,%2};" :: "r"(a), "r"(x), "r"(y) : "memory"); }

template <int KSTRIDE>
__device__ __forceinline__ void proj512(float (&out)[4], uint32_t a_addr, uint32_t x_addr) {
    float acc[4][4];
#pragma unroll
    for (int i = 0; i < 4; i++) { acc[i][0] = acc[i][1] = acc[i][2] = acc[i][3] = 0.f; }
#pragma unroll 4
    for (int k2 = 0; k2 < 16; k2++) {
        uint32_t b[4], a0[4], a1[4];
        ldsm4(b, x_addr + k2 * 64);
        ldsm4t(a0, a_addr + (2 * k2) * KSTRIDE);
        ldsm4t(a1, a_addr + (2 * k2 + 1) * KSTRIDE);
        mma16816(acc[(2 * k2) & 3], a0, b[0], b[1]);
        mma16816(acc[(2 * k2 + 1) & 3], a1, b[2], b[3]);
    }
#pragma unroll
    for (int i = 0; i < 4; i++) out[i] = (acc[0][i] + acc[1][i]) + (acc[2][i] + acc[3][i]);
}

__global__ void __launch_bounds__(NTHREADS, 1)
fused_decode_kernel(const __grid_constant__ CUtensorMap mapK, const __grid_constant__ CUtensorMap mapV,
                    const __grid_constant__ CUtensorMap mapWq, const __grid_constant__ CUtensorMap mapWg,
                    const __grid_constant__ CUtensorMap mapWu, const __grid_constant__ CUtensorMap mapWd,
                    const __grid_constant__ CUtensorMap mapWo,
                    const __nv_bfloat16* __restrict__ x, const __nv_bfloat16* __restrict__ gate_w,
                    __nv_bfloat16* __restrict__ out)
{
    extern __shared__ uint8_t smem_raw[];
    const uint32_t sb = (smem_u32(smem_raw) + 1023u) & ~1023u;
    const int cta = blockIdx.x, tid = threadIdx.x, warp = tid >> 5, lane = tid & 31;
    const bool ffn = cta < NFFN;
    const uint32_t bar_full = sb + OFF_BAR, bar_empty = sb + OFF_BAR + 8 * NSTAGES;

    if (warp == 4) {
        const int nitems = (ffn ? 2 : 1) + 2 * NTILES + (ffn ? 2 : 1);
        const int base = ffn ? 2 : 1;
        auto issue = [&](int it, int st) {
            const uint32_t dst = sb + st * STAGE_BYTES, bar = bar_full + 8 * st;
            const int j = it - base;
            if (j >= 0 && j < 2 * NTILES) {
                mbar_expect_tx(bar, STAGE_BYTES);
                const int row = cta * 4096 + (j >> 1) * TILE;
                tma3d(dst, (j & 1) ? &mapV : &mapK, 0, row, 0, bar);
            } else if (it == 0) {
                mbar_expect_tx(bar, STAGE_BYTES + 4096);
                tma2d(dst, &mapWq, cta * 32, 0, bar);
                tma2d(dst + 16384, &mapWq, cta * 32, 256, bar);
#pragma unroll
                for (int b = 0; b < 4; b++) bulk_load(sb + OFF_XS + b * XS_STRIDE, x + b * 512, 1024, bar);
            } else if (j < 0) {
                mbar_expect_tx(bar, STAGE_BYTES);
                tma2d(dst,         &mapWg, cta * 16, 0,   bar);
                tma2d(dst + 8192,  &mapWg, cta * 16, 256, bar);
                tma2d(dst + 16384, &mapWu, cta * 16, 0,   bar);
                tma2d(dst + 24576, &mapWu, cta * 16, 256, bar);
            } else if (ffn && j == 2 * NTILES) {
                mbar_expect_tx(bar, 16384);
                tma3d(dst, &mapWd, 0, (cta >> 2) * 64, (cta & 3) * 2, bar);
            } else {
                mbar_expect_tx(bar, STAGE_BYTES);
                tma3d(dst, &mapWo, 0, (cta >> 2) * 128, (cta & 3) * 2, bar);
            }
        };
        if (lane == 0) {
            PROFP(0);
#pragma unroll
            for (int i = 0; i < NSTAGES; i++) { mbar_init(bar_full + 8 * i, 1); mbar_init(bar_empty + 8 * i, 4); }
            asm volatile("fence.mbarrier_init.release.cluster;" ::: "memory");
            asm volatile("fence.proxy.async.shared::cta;" ::: "memory");
            for (int i = 0; i < WINDOW; i++) issue(i, i);
            prefetch_map(&mapWd);
            prefetch_map(&mapWo);
        }
        __syncwarp();
        __syncthreads();
        if (lane == 0) {
            int st = WINDOW, ph = 1, fst = 0, fph = 0;
            for (int it = WINDOW; it < nitems; it++) {
                mbar_wait(bar_full + 8 * fst, fph, 200 + it);
                if (++fst == NSTAGES) { fst = 0; fph ^= 1; }
                if (it >= NSTAGES) mbar_wait(bar_empty + 8 * st, ph, 100 + it);
                issue(it, st);
                if (++st == NSTAGES) { st = 0; ph ^= 1; }
            }
            PROFP(1);
        }
        return;
    }

    const uint32_t epoch = *(volatile const uint32_t*)&g_epoch[cta];
    const uint4 gw0 = __ldg(reinterpret_cast<const uint4*>(gate_w) + lane * 2);
    const uint4 gw1 = __ldg(reinterpret_cast<const uint4*>(gate_w) + lane * 2 + 1);
    __syncthreads();
    const uint32_t tag32 = epoch + 1u, tag16 = tag32 & 0xffffu, tag1 = tag32 & 1u;

    const int r = lane >> 2, c = lane & 3;
    const int bq = cta >> 5, hkv = (cta >> 2) & 7, sq = cta & 3;
    const int kk = cta >> 2, nn = cta & 3;
    int st = 0, ph = 0;
    auto advance = [&]() { if (++st == NSTAGES) { st = 0; ph ^= 1; } };
    auto release = [&]() { __syncwarp(); if (lane == 0) mbar_arrive(bar_empty + 8 * st); };

    const uint32_t xs_lane = sb + OFF_XS + (lane & 3) * XS_STRIDE + (lane >> 3) * 16;

    mbar_wait(bar_full, 0, 1);
    PROF(2);
    if (warp < 2) {
        float d[4];
        const int k = (lane & 7) + 8 * (lane >> 4);
        const int cc = 2 * warp + ((lane >> 3) & 1);
        proj512<1024>(d, sb + k * 64 + ((cc ^ ((lane & 7) >> 1)) << 4), xs_lane);
        const float v0 = (c >= 2) ? d[2] : d[0], v1 = (c >= 2) ? d[3] : d[1];
        uint32_t* dst = g_q + (2 * (c & 1)) * 4096 + cta * 32 + warp * 16 + r + 8 * (c >> 1);
        stg_rlx(dst, (bf16bits(v0) << 16) | tag16);
        stg_rlx(dst + 4096, (bf16bits(v1) << 16) | tag16);
        PROF(11);
    }
    release(); advance();
    if (ffn) {
        if (warp >= 2) {
            mbar_wait(bar_full + 8 * st, ph, 2);
            PROFW(2, 13);
            float d[4];
            const int k = (lane & 7) + 8 * (lane >> 4);
            const int cc = (lane >> 3) & 1;
            proj512<512>(d, sb + st * STAGE_BYTES + (warp - 2) * 16384 + k * 32 + ((cc ^ ((lane & 7) >> 2)) << 4), xs_lane);
            const float v0 = bf16r((c >= 2) ? d[2] : d[0]), v1 = bf16r((c >= 2) ? d[3] : d[1]);
            release();
            if (warp == 3) { sts_f32(sb + OFF_UP + lane * 8, v0); sts_f32(sb + OFF_UP + lane * 8 + 4, v1); }
            bar_sync(2, 64);
            if (warp == 2) {
                const float u0 = lds_f32(sb + OFF_UP + lane * 8), u1 = lds_f32(sb + OFF_UP + lane * 8 + 4);
                const float h0 = (v0 > 0.f ? v0 : 0.f * v0) * u0, h1 = (v1 > 0.f ? v1 : 0.f * v1) * u1;
                uint32_t* dst = g_h + (2 * (c & 1)) * 1792 + cta * 16 + r + 8 * (c >> 1);
                stg_rlx(dst, (bf16bits(h0) << 16) | tag16);
                stg_rlx(dst + 1792, (bf16bits(h1) << 16) | tag16);
                PROFW(2, 15);
            }
        } else {
            release();
        }
    }
    {
        const uint4 x0 = lds_u32x4(sb + OFF_XS + warp * XS_STRIDE + lane * 32);
        const uint4 x1 = lds_u32x4(sb + OFF_XS + warp * XS_STRIDE + lane * 32 + 16);
        const uint32_t xv[8] = {x0.x, x0.y, x0.z, x0.w, x1.x, x1.y, x1.z, x1.w};
        const uint32_t wv[8] = {gw0.x, gw0.y, gw0.z, gw0.w, gw1.x, gw1.y, gw1.z, gw1.w};
        float z = 0.f;
#pragma unroll
        for (int i = 0; i < 8; i++) {
            const __nv_bfloat162 p = __hmul2(*reinterpret_cast<const __nv_bfloat162*>(&xv[i]), *reinterpret_cast<const __nv_bfloat162*>(&wv[i]));
            z += __low2float(p) + __high2float(p);
        }
#pragma unroll
        for (int o = 16; o > 0; o >>= 1) z += __shfl_xor_sync(0xffffffffu, z, o);
        z = bf16r(z);
        const float g = bf16r(1.f / (1.f + expf(-z)));
        if (lane == 0) { sts_f32(sb + OFF_GS + warp * 4, g); sts_f32(sb + OFF_GS + 16 + warp * 4, bf16r(1.f - g)); }
    }
    {
        const uint32_t* src = g_q + bq * 4096 + (hkv * 4 + warp) * 128 + lane * 4;
        uint4 v; int it = 0;
        while (true) {
            v = ldg_rlx4(src);
            const bool ok = ((v.x & 0xffffu) == tag16) && ((v.y & 0xffffu) == tag16) && ((v.z & 0xffffu) == tag16) && ((v.w & 0xffffu) == tag16);
            if (__all_sync(0xffffffffu, ok)) break;
            if (++it > SPIN_LIMIT) SPIN_FAIL(21);
        }
        sts_u32x2(sb + OFF_QS + warp * QS_STRIDE + lane * 8, __byte_perm(v.x, v.y, 0x7632), __byte_perm(v.z, v.w, 0x7632));
        PROF(12);
    }
    if (ffn) {
        if (warp < 2) {
            const int b = tid >> 4, f4 = (tid & 15) * 4;
            const uint32_t* src = g_h + b * 1792 + kk * 64 + f4;
            uint4 v; int it = 0;
            while (true) {
                v = ldg_rlx4(src);
                const bool ok = ((v.x & 0xffffu) == tag16) && ((v.y & 0xffffu) == tag16) && ((v.z & 0xffffu) == tag16) && ((v.w & 0xffffu) == tag16);
                if (__all_sync(0xffffffffu, ok)) break;
                if (++it > SPIN_LIMIT) SPIN_FAIL(22);
            }
            sts_u32x2(sb + OFF_HS + b * HS_STRIDE + f4 * 2, __byte_perm(v.x, v.y, 0x7632), __byte_perm(v.z, v.w, 0x7632));
            PROF(14);
        }
        advance();
    }
    bar_sync(1, 128);
    PROF(3);
    uint32_t qf[8][2];
#pragma unroll
    for (int k2 = 0; k2 < 4; k2++) {
        uint32_t b[4];
        ldsm4(b, sb + OFF_QS + (lane & 3) * QS_STRIDE + (lane >> 3) * 16 + k2 * 64);
        qf[2 * k2][0] = b[0]; qf[2 * k2][1] = b[1]; qf[2 * k2 + 1][0] = b[2]; qf[2 * k2 + 1][1] = b[3];
    }

    const float sl2 = 0.08838834764831845f * 1.4426950408889634f;
    float O[8][4];
#pragma unroll
    for (int t = 0; t < 8; t++) { O[t][0] = O[t][1] = O[t][2] = O[t][3] = 0.f; }
    float m0 = -INFINITY, m1 = -INFINITY, l0 = 0.f, l1 = 0.f;
    const uint32_t offK = (32 * warp + (lane & 7) + 8 * ((lane >> 3) & 1)) * 128 + (((lane >> 4) ^ (lane & 7)) << 4);
    const uint32_t offV = (32 * warp + (lane & 7) + 8 * (lane >> 4)) * 128 + ((((lane >> 3) & 1) ^ (lane & 7)) << 4);

#pragma unroll 1
    for (int tile = 0; tile < NTILES; tile++) {
        float s[2][2][4];
        {
            const uint32_t kb = sb + st * STAGE_BYTES;
            mbar_wait(bar_full + 8 * st, ph, 4);
#pragma unroll
            for (int j = 0; j < 2; j++)
#pragma unroll
                for (int h = 0; h < 2; h++) { s[j][h][0] = s[j][h][1] = s[j][h][2] = s[j][h][3] = 0.f; }
#pragma unroll
            for (int ks = 0; ks < 8; ks++) {
#pragma unroll
                for (int j = 0; j < 2; j++) {
                    uint32_t a[4];
                    ldsm4(a, kb + (offK ^ ((ks & 3) << 5)) + (ks >> 2) * 16384 + j * 2048);
                    mma16816(s[j][ks & 1], a, qf[ks][0], qf[ks][1]);
                }
            }
            release(); advance();
        }
        float v[2][4];
#pragma unroll
        for (int j = 0; j < 2; j++)
#pragma unroll
            for (int i = 0; i < 4; i++) v[j][i] = s[j][0][i] + s[j][1][i];
        float mx0 = fmaxf(fmaxf(v[0][0], v[0][2]), fmaxf(v[1][0], v[1][2]));
        float mx1 = fmaxf(fmaxf(v[0][1], v[0][3]), fmaxf(v[1][1], v[1][3]));
#pragma unroll
        for (int o = 4; o < 32; o <<= 1) {
            mx0 = fmaxf(mx0, __shfl_xor_sync(0xffffffffu, mx0, o));
            mx1 = fmaxf(mx1, __shfl_xor_sync(0xffffffffu, mx1, o));
        }
        const float mn0 = fmaxf(m0, mx0 * sl2), mn1 = fmaxf(m1, mx1 * sl2);
        const float al0 = ex2(m0 - mn0), al1 = ex2(m1 - mn1);
        m0 = mn0; m1 = mn1;
        uint32_t pb[2][2];
        float ps0 = 0.f, ps1 = 0.f;
#pragma unroll
        for (int j = 0; j < 2; j++) {
            const float p0 = ex2(fmaf(v[j][0], sl2, -mn0)), p1 = ex2(fmaf(v[j][1], sl2, -mn1));
            const float p2 = ex2(fmaf(v[j][2], sl2, -mn0)), p3 = ex2(fmaf(v[j][3], sl2, -mn1));
            ps0 += p0 + p2; ps1 += p1 + p3;
            pb[j][0] = movm_t(pack_bf16(p0, p1));
            pb[j][1] = movm_t(pack_bf16(p2, p3));
        }
        l0 = l0 * al0 + ps0; l1 = l1 * al1 + ps1;
#pragma unroll
        for (int t = 0; t < 8; t++) { O[t][0] *= al0; O[t][1] *= al1; O[t][2] *= al0; O[t][3] *= al1; }
        {
            const uint32_t vb = sb + st * STAGE_BYTES;
            mbar_wait(bar_full + 8 * st, ph, 5);
#pragma unroll
            for (int j = 0; j < 2; j++) {
#pragma unroll
                for (int t = 0; t < 8; t++) {
                    uint32_t a[4];
                    ldsm4t(a, vb + (offV ^ ((t & 3) << 5)) + (t >> 2) * 16384 + j * 2048);
                    mma16816(O[t], a, pb[j][0], pb[j][1]);
                }
            }
            release(); advance();
        }
    }
    PROF(4);

#pragma unroll
    for (int o = 4; o < 32; o <<= 1) {
        l0 += __shfl_xor_sync(0xffffffffu, l0, o);
        l1 += __shfl_xor_sync(0xffffffffu, l1, o);
    }
    {
        const uint32_t so = sb + OFF_SO + ((warp * 4 + 2 * (c & 1)) * SO_STRIDE + 8 * (c >> 1) + r) * 4;
#pragma unroll
        for (int t = 0; t < 8; t++) {
            sts_f32(so + t * 64, (c >= 2) ? O[t][2] : O[t][0]);
            sts_f32(so + t * 64 + SO_STRIDE * 4, (c >= 2) ? O[t][3] : O[t][1]);
        }
        if (lane < 2) {
            const uint32_t sm = sb + OFF_SM + (warp * 4 + 2 * lane) * 4;
            sts_f32(sm, m0); sts_f32(sm + 4, m1); sts_f32(sm + 64, l0); sts_f32(sm + 68, l1);
        }
    }
    bar_sync(1, 128);
    {
        float mw[4], lw[4];
#pragma unroll
        for (int w = 0; w < 4; w++) { mw[w] = lds_f32(sb + OFF_SM + (w * 4 + warp) * 4); lw[w] = lds_f32(sb + OFF_SM + 64 + (w * 4 + warp) * 4); }
        const float M = fmaxf(fmaxf(mw[0], mw[1]), fmaxf(mw[2], mw[3]));
        float4 acc = make_float4(0.f, 0.f, 0.f, 0.f); float L = 0.f;
#pragma unroll
        for (int w = 0; w < 4; w++) {
            const float sc = ex2(mw[w] - M);
            const float4 o = lds_f32x4(sb + OFF_SO + ((w * 4 + warp) * SO_STRIDE + lane * 4) * 4);
            acc.x = fmaf(sc, o.x, acc.x); acc.y = fmaf(sc, o.y, acc.y); acc.z = fmaf(sc, o.z, acc.z); acc.w = fmaf(sc, o.w, acc.w);
            L = fmaf(sc, lw[w], L);
        }
        const int slot = (bq * 32 + hkv * 4 + warp) * 4 + sq;
        stg_rlx4(g_part + slot * 128 + lane * 4,
                 (__float_as_uint(acc.x) & ~1u) | tag1, (__float_as_uint(acc.y) & ~1u) | tag1,
                 (__float_as_uint(acc.z) & ~1u) | tag1, (__float_as_uint(acc.w) & ~1u) | tag1);
        if (lane == 0)
            stg_rlx2x64(g_ml + slot * 2, ((unsigned long long)__float_as_uint(M) << 32) | tag32, ((unsigned long long)__float_as_uint(L) << 32) | tag32);
    }
    PROF(5);

    float yb[2][4], ya[2][2][4];
#pragma unroll
    for (int i = 0; i < 2; i++) { yb[i][0] = yb[i][1] = yb[i][2] = yb[i][3] = 0.f;
#pragma unroll
        for (int j = 0; j < 2; j++) { ya[i][j][0] = ya[i][j][1] = ya[i][j][2] = ya[i][j][3] = 0.f; } }
    const uint32_t offA = ((lane & 7) + 8 * (lane >> 4)) * 128;
    const uint32_t swz0 = ((2 * ((2 * warp) & 3) + ((lane >> 3) & 1)) ^ (lane & 7)) << 4;
    const uint32_t swz1 = ((2 * ((2 * warp + 1) & 3) + ((lane >> 3) & 1)) ^ (lane & 7)) << 4;
    if (ffn) {
        uint32_t hb[2][4];
        ldsm4(hb[0], sb + OFF_HS + (lane & 3) * HS_STRIDE + (lane >> 3) * 16);
        ldsm4(hb[1], sb + OFF_HS + (lane & 3) * HS_STRIDE + (lane >> 3) * 16 + 64);
        mbar_wait(bar_full + 8 * st, ph, 6);
        const uint32_t base = sb + st * STAGE_BYTES + (warp >> 1) * 8192 + offA;
#pragma unroll
        for (int ks = 0; ks < 4; ks++) {
            uint32_t a0[4], a1[4];
            ldsm4t(a0, base + ks * 2048 + swz0);
            ldsm4t(a1, base + ks * 2048 + swz1);
            mma16816(yb[0], a0, hb[ks >> 1][2 * (ks & 1)], hb[ks >> 1][2 * (ks & 1) + 1]);
            mma16816(yb[1], a1, hb[ks >> 1][2 * (ks & 1)], hb[ks >> 1][2 * (ks & 1) + 1]);
        }
        advance();
    }
    PROF(6);

    {
        const int slot0 = (warp * 32 + kk) * 4;
        uint4 ov[4]; ulonglong2 ml[4];
        int it = 0;
        while (true) {
            bool ok = true;
#pragma unroll
            for (int s = 0; s < 4; s++) {
                ov[s] = ldg_rlx4(g_part + (slot0 + s) * 128 + lane * 4);
                ml[s] = ldg_rlx2x64(g_ml + (slot0 + s) * 2);
            }
#pragma unroll
            for (int s = 0; s < 4; s++) {
                ok = ok && (((ov[s].x ^ tag1) & 1u) == 0) && (((ov[s].y ^ tag1) & 1u) == 0) && (((ov[s].z ^ tag1) & 1u) == 0) && (((ov[s].w ^ tag1) & 1u) == 0);
                ok = ok && ((uint32_t)ml[s].x == tag32) && ((uint32_t)ml[s].y == tag32);
            }
            if (__all_sync(0xffffffffu, ok)) break;
            if (++it > SPIN_LIMIT) SPIN_FAIL(23);
        }
        float Ms[4], M = -INFINITY;
#pragma unroll
        for (int s = 0; s < 4; s++) { Ms[s] = __uint_as_float((uint32_t)(ml[s].x >> 32)); M = fmaxf(M, Ms[s]); }
        float L = 0.f, a0 = 0.f, a1 = 0.f, a2 = 0.f, a3 = 0.f;
#pragma unroll
        for (int s = 0; s < 4; s++) {
            const float w = ex2(Ms[s] - M);
            L  = fmaf(w, __uint_as_float((uint32_t)(ml[s].y >> 32)), L);
            a0 = fmaf(w, __uint_as_float(ov[s].x), a0); a1 = fmaf(w, __uint_as_float(ov[s].y), a1);
            a2 = fmaf(w, __uint_as_float(ov[s].z), a2); a3 = fmaf(w, __uint_as_float(ov[s].w), a3);
        }
        const float inv = 1.f / L;
        sts_u32x2(sb + OFF_OS + warp * QS_STRIDE + lane * 8, pack_bf16(a0 * inv, a1 * inv), pack_bf16(a2 * inv, a3 * inv));
    }
    PROF(7);
    bar_sync(1, 128);
    {
        uint32_t ob[4][4];
#pragma unroll
        for (int k2 = 0; k2 < 4; k2++) ldsm4(ob[k2], sb + OFF_OS + (lane & 3) * QS_STRIDE + (lane >> 3) * 16 + k2 * 64);
        mbar_wait(bar_full + 8 * st, ph, 7);
        const uint32_t base = sb + st * STAGE_BYTES + (warp >> 1) * 16384 + offA;
#pragma unroll
        for (int ks = 0; ks < 8; ks++) {
            uint32_t a0[4], a1[4];
            ldsm4t(a0, base + ks * 2048 + swz0);
            ldsm4t(a1, base + ks * 2048 + swz1);
            mma16816(ya[0][ks & 1], a0, ob[ks >> 1][2 * (ks & 1)], ob[ks >> 1][2 * (ks & 1) + 1]);
            mma16816(ya[1][ks & 1], a1, ob[ks >> 1][2 * (ks & 1)], ob[ks >> 1][2 * (ks & 1) + 1]);
        }
        const int b0 = 2 * (c & 1);
        const float g0 = lds_f32(sb + OFF_GS + b0 * 4), g1 = lds_f32(sb + OFF_GS + b0 * 4 + 4);
        const float f0 = lds_f32(sb + OFF_GS + 16 + b0 * 4), f1 = lds_f32(sb + OFF_GS + 16 + b0 * 4 + 4);
#pragma unroll
        for (int i = 0; i < 2; i++) {
            const int e = (c >= 2) ? 2 : 0;
            const float av0 = (e ? ya[i][0][2] + ya[i][1][2] : ya[i][0][0] + ya[i][1][0]);
            const float av1 = (e ? ya[i][0][3] + ya[i][1][3] : ya[i][0][1] + ya[i][1][1]);
            const float bv0 = e ? yb[i][2] : yb[i][0], bv1 = e ? yb[i][3] : yb[i][1];
            const float y0 = fmaf(g0, av0, f0 * bv0), y1 = fmaf(g1, av1, f1 * bv1);
            const int cg = nn * 8 + warp * 2 + i;
            uint32_t* dst = g_y + ((b0 * 32 + cg) * 32 + kk) * 16 + r + 8 * (c >> 1);
            stg_rlx(dst, (__float_as_uint(y0) & ~1u) | tag1);
            stg_rlx(dst + 32 * 32 * 16, (__float_as_uint(y1) & ~1u) | tag1);
        }
    }
    PROF(8);
    if (warp == 0) {
        const uint32_t* src = g_y + (cta * 32 + r) * 16 + c * 4;
        uint4 v[4]; int it = 0;
        while (true) {
            bool ok = true;
#pragma unroll
            for (int i = 0; i < 4; i++) v[i] = ldg_rlx4(src + i * 8 * 16);
#pragma unroll
            for (int i = 0; i < 4; i++)
                ok = ok && (((v[i].x ^ tag1) & 1u) == 0) && (((v[i].y ^ tag1) & 1u) == 0) && (((v[i].z ^ tag1) & 1u) == 0) && (((v[i].w ^ tag1) & 1u) == 0);
            if (__all_sync(0xffffffffu, ok)) break;
            if (++it > SPIN_LIMIT) SPIN_FAIL(24);
        }
        float s0 = 0.f, s1 = 0.f, s2 = 0.f, s3 = 0.f;
#pragma unroll
        for (int i = 0; i < 4; i++) { s0 += __uint_as_float(v[i].x); s1 += __uint_as_float(v[i].y); s2 += __uint_as_float(v[i].z); s3 += __uint_as_float(v[i].w); }
#pragma unroll
        for (int o = 4; o < 32; o <<= 1) {
            s0 += __shfl_xor_sync(0xffffffffu, s0, o); s1 += __shfl_xor_sync(0xffffffffu, s1, o);
            s2 += __shfl_xor_sync(0xffffffffu, s2, o); s3 += __shfl_xor_sync(0xffffffffu, s3, o);
        }
        if (lane < 4) {
            uint2 o2 = make_uint2(pack_bf16(s0, s1), pack_bf16(s2, s3));
            *reinterpret_cast<uint2*>(out + cta * 16 + lane * 4) = o2;
        }
        if (lane == 0) g_epoch[cta] = epoch + 1u;
        PROF(9);
    }
}

typedef CUresult (*EncodeFn)(CUtensorMap*, CUtensorMapDataType, cuuint32_t, void*, const cuuint64_t*, const cuuint64_t*,
                             const cuuint32_t*, const cuuint32_t*, CUtensorMapInterleave, CUtensorMapSwizzle,
                             CUtensorMapL2promotion, CUtensorMapFloatOOBfill);

void make_map(EncodeFn enc, CUtensorMap* m, const void* p, int rank, cuuint64_t d0, cuuint64_t d1, cuuint64_t d2,
              cuuint64_t s1, cuuint64_t s2, cuuint32_t b0, cuuint32_t b1, cuuint32_t b2, CUtensorMapSwizzle sw) {
    cuuint64_t dims[3] = {d0, d1, d2}, strides[2] = {s1, s2};
    cuuint32_t box[3] = {b0, b1, b2}, es[3] = {1, 1, 1};
    enc(m, CU_TENSOR_MAP_DATA_TYPE_BFLOAT16, rank, const_cast<void*>(p), dims, strides, box, es,
        CU_TENSOR_MAP_INTERLEAVE_NONE, sw, CU_TENSOR_MAP_L2_PROMOTION_L2_256B, CU_TENSOR_MAP_FLOAT_OOB_FILL_NONE);
}

}

extern "C" void kernel_launch(void* const* d_in, const int* in_sizes, int n_in, void* d_out, int out_size) {
    (void)in_sizes; (void)n_in; (void)out_size;
    static EncodeFn enc = nullptr;
    if (!enc) {
        void* fn = nullptr;
        cudaDriverEntryPointQueryResult qr;
        cudaGetDriverEntryPoint("cuTensorMapEncodeTiled", &fn, cudaEnableDefault, &qr);
        enc = (EncodeFn)fn;
        cudaFuncSetAttribute(fused_decode_kernel, cudaFuncAttributeMaxDynamicSharedMemorySize, SMEM_BYTES);
    }
    CUtensorMap mK, mV, mWq, mWg, mWu, mWd, mWo;
    make_map(enc, &mK, d_in[1], 3, 64, 4 * 8 * 16384, 2, 256, 128, 64, TILE, 2, CU_TENSOR_MAP_SWIZZLE_128B);
    make_map(enc, &mV, d_in[2], 3, 64, 4 * 8 * 16384, 2, 256, 128, 64, TILE, 2, CU_TENSOR_MAP_SWIZZLE_128B);
    make_map(enc, &mWq, d_in[3], 2, 4096, 512, 1, 8192, 0, 32, 256, 1, CU_TENSOR_MAP_SWIZZLE_64B);
    make_map(enc, &mWg, d_in[6], 2, 1792, 512, 1, 3584, 0, 16, 256, 1, CU_TENSOR_MAP_SWIZZLE_32B);
    make_map(enc, &mWu, d_in[7], 2, 1792, 512, 1, 3584, 0, 16, 256, 1, CU_TENSOR_MAP_SWIZZLE_32B);
    make_map(enc, &mWd, d_in[8], 3, 64, 1792, 8, 1024, 128, 64, 64, 2, CU_TENSOR_MAP_SWIZZLE_128B);
    make_map(enc, &mWo, d_in[4], 3, 64, 4096, 8, 1024, 128, 64, 128, 2, CU_TENSOR_MAP_SWIZZLE_128B);
    fused_decode_kernel<<<NCTA, NTHREADS, SMEM_BYTES>>>(mK, mV, mWq, mWg, mWu, mWd, mWo,
        (const __nv_bfloat16*)d_in[0], (const __nv_bfloat16*)d_in[9], (__nv_bfloat16*)d_out);
}
```

```cpp
#include <cuda_runtime.h>
#include <cuda_bf16.h>
#include <cuda.h>
#include <stdint.h>

namespace {

constexpr int NCTA        = 128;
constexpr int NTHREADS    = 160;
constexpr int STAGE_BYTES = 32768;
#define NSTAGES 6
#define WINDOW 2
static_assert(WINDOW < NSTAGES, "window must be smaller than the ring");
constexpr int TILE   = 128;
constexpr int NTILES = 4096 / TILE;
constexpr int NFFN   = 112;
#define TILE_WD 32
#define TILE_H 6
#define FLAG_LEAD 0
#define RAMP1 0
#define RAMP2 0
#define RAMP3 0
#define LEADX 384
#define BOOSTX 9999
#define BOOST2 9999
#define LATE_FLAG 0
#define INIT_ITEMS 2
#define GLOBAL_FLAG 1
#define GATE1 1
#define PFL 1
#define PFL_STRIDE 256
#define INIT_ORDER 0
#define PF0 0
#define TILE_PRE 99
constexpr bool WD_TAIL = TILE_WD >= NTILES;
constexpr int IT_WG = 3;
constexpr int IT_WD = 2 * TILE_WD + 2;
static_assert(WD_TAIL || TILE_H <= TILE_WD, "h must be gathered before W_down is consumed");

constexpr int OFF_BAR = NSTAGES * STAGE_BYTES;
constexpr int OFF_XS  = OFF_BAR + 256;
constexpr int XS_STRIDE = 1040;
constexpr int OFF_QS  = OFF_XS + 4 * XS_STRIDE;
constexpr int QS_STRIDE = 272;
constexpr int OFF_OS  = OFF_QS + 4 * QS_STRIDE;
constexpr int OFF_HS  = OFF_OS + 4 * QS_STRIDE;
constexpr int HS_STRIDE = 144;
constexpr int OFF_SO  = OFF_HS + 4 * HS_STRIDE;
constexpr int SO_STRIDE = 136;
constexpr int OFF_SM  = OFF_SO + 16 * SO_STRIDE * 4;
constexpr int OFF_GS  = OFF_SM + 128;
constexpr int OFF_UP  = OFF_GS + 32;
constexpr int SMEM_USED  = OFF_UP + 256;
constexpr int SMEM_BYTES = SMEM_USED + 1024;

__device__ uint32_t g_epoch[NCTA];
__device__ __align__(128) uint32_t g_q[4 * 4096];
__device__ __align__(128) uint32_t g_h[4 * 1792];
__device__ __align__(128) uint32_t g_part[4 * 32 * 4 * 128];
__device__ __align__(128) unsigned long long g_ml[4 * 32 * 4 * 2];
__device__ __align__(128) uint32_t g_y[4 * 32 * 32 * 16];
__device__ __align__(128) uint32_t g_cnt;
__device__ __align__(128) uint32_t g_flag1[NCTA];
__device__ __align__(128) uint32_t g_flag2[NCTA];

#define PROFW(w, i)
#define PROF(i)
#define PROFP(i)

constexpr int SPIN_LIMIT = 1 << 22;
#define SPIN_FAIL(code) __trap()

__device__ __forceinline__ uint32_t smem_u32(const void* p) { return (uint32_t)__cvta_generic_to_shared(p); }
__device__ __forceinline__ void mbar_init(uint32_t bar, uint32_t cnt) {
    asm volatile("mbarrier.init.shared::cta.b64 [%0], %1;" :: "r"(bar), "r"(cnt) : "memory");
}
__device__ __forceinline__ void mbar_expect_tx(uint32_t bar, uint32_t bytes) {
    asm volatile("mbarrier.arrive.expect_tx.shared::cta.b64 _, [%0], %1;" :: "r"(bar), "r"(bytes) : "memory");
}
__device__ __forceinline__ void mbar_arrive(uint32_t bar) {
    asm volatile("mbarrier.arrive.shared::cta.b64 _, [%0];" :: "r"(bar) : "memory");
}
__device__ __forceinline__ bool mbar_try_wait(uint32_t bar, uint32_t parity) {
    uint32_t ok;
    asm volatile("{\n.reg .pred p;\nmbarrier.try_wait.parity.shared::cta.b64 p, [%1], %2;\nselp.u32 %0, 1, 0, p;\n}"
                 : "=r"(ok) : "r"(bar), "r"(parity) : "memory");
    return ok;
}
__device__ __forceinline__ void mbar_wait(uint32_t bar, uint32_t parity, int code = 0) {
    int it = 0;
    while (!mbar_try_wait(bar, parity)) { if (++it > SPIN_LIMIT) SPIN_FAIL(code); }
}
__device__ __forceinline__ bool mbar_test(uint32_t bar, uint32_t parity) {
    uint32_t ok;
    asm volatile("{\n.reg .pred p;\nmbarrier.test_wait.parity.shared::cta.b64 p, [%1], %2;\nselp.u32 %0, 1, 0, p;\n}"
                 : "=r"(ok) : "r"(bar), "r"(parity) : "memory");
    return ok;
}
__device__ __forceinline__ void bulk_load(uint32_t dst, const void* src, uint32_t bytes, uint32_t bar) {
    asm volatile("cp.async.bulk.shared::cluster.global.mbarrier::complete_tx::bytes [%0], [%1], %2, [%3];"
                 :: "r"(dst), "l"(src), "r"(bytes), "r"(bar) : "memory");
}
__device__ __forceinline__ void tma2d(uint32_t dst, const CUtensorMap* tm, int c0, int c1, uint32_t bar) {
    asm volatile("cp.async.bulk.tensor.2d.shared::cluster.global.mbarrier::complete_tx::bytes [%0], [%1, {%3, %4}], [%2];"
                 :: "r"(dst), "l"(tm), "r"(bar), "r"(c0), "r"(c1) : "memory");
}
__device__ __forceinline__ void tma3d(uint32_t dst, const CUtensorMap* tm, int c0, int c1, int c2, uint32_t bar) {
    asm volatile("cp.async.bulk.tensor.3d.shared::cluster.global.mbarrier::complete_tx::bytes [%0], [%1, {%3, %4, %5}], [%2];"
                 :: "r"(dst), "l"(tm), "r"(bar), "r"(c0), "r"(c1), "r"(c2) : "memory");
}
__device__ __forceinline__ void prefetch_l2(const void* p, uint32_t bytes) {
    asm volatile("cp.async.bulk.prefetch.L2.global [%0], %1;" :: "l"(p), "r"(bytes) : "memory");
}
__device__ __forceinline__ void prefetch_map(const CUtensorMap* tm) {
    asm volatile("prefetch.tensormap [%0];" :: "l"(tm) : "memory");
}
__device__ __forceinline__ void ldsm4(uint32_t (&r)[4], uint32_t addr) {
    asm volatile("ldmatrix.sync.aligned.m8n8.x4.shared.b16 {%0,%1,%2,%3}, [%4];"
                 : "=r"(r[0]), "=r"(r[1]), "=r"(r[2]), "=r"(r[3]) : "r"(addr) : "memory");
}
__device__ __forceinline__ void ldsm4t(uint32_t (&r)[4], uint32_t addr) {
    asm volatile("ldmatrix.sync.aligned.m8n8.x4.trans.shared.b16 {%0,%1,%2,%3}, [%4];"
                 : "=r"(r[0]), "=r"(r[1]), "=r"(r[2]), "=r"(r[3]) : "r"(addr) : "memory");
}
__device__ __forceinline__ void mma16816(float (&d)[4], const uint32_t (&a)[4], uint32_t b0, uint32_t b1) {
    asm volatile("mma.sync.aligned.m16n8k16.row.col.f32.bf16.bf16.f32 {%0,%1,%2,%3}, {%4,%5,%6,%7}, {%8,%9}, {%0,%1,%2,%3};"
                 : "+f"(d[0]), "+f"(d[1]), "+f"(d[2]), "+f"(d[3])
                 : "r"(a[0]), "r"(a[1]), "r"(a[2]), "r"(a[3]), "r"(b0), "r"(b1));
}
__device__ __forceinline__ uint32_t movm_t(uint32_t a) {
    uint32_t d;
    asm volatile("movmatrix.sync.aligned.m8n8.trans.b16 %0, %1;" : "=r"(d) : "r"(a));
    return d;
}
__device__ __forceinline__ uint32_t pack_bf16(float lo, float hi) {
    uint32_t d;
    asm("cvt.rn.bf16x2.f32 %0, %1, %2;" : "=r"(d) : "f"(hi), "f"(lo));
    return d;
}
__device__ __forceinline__ float ex2(float x) {
    float y;
    asm("ex2.approx.ftz.f32 %0, %1;" : "=f"(y) : "f"(x));
    return y;
}
__device__ __forceinline__ float bf16r(float x) { return __bfloat162float(__float2bfloat16_rn(x)); }
__device__ __forceinline__ uint32_t bf16bits(float x) { return (uint32_t)__bfloat16_as_ushort(__float2bfloat16_rn(x)); }
__device__ __forceinline__ void bar_sync(int id, int n) { asm volatile("bar.sync %0, %1;" :: "r"(id), "r"(n) : "memory"); }

__device__ __forceinline__ uint4 ldg_rlx4(const uint32_t* p) {
    uint4 v;
    asm volatile("ld.relaxed.gpu.global.v4.u32 {%0,%1,%2,%3}, [%4];" : "=r"(v.x), "=r"(v.y), "=r"(v.z), "=r"(v.w) : "l"(p) : "memory");
    return v;
}
__device__ __forceinline__ ulonglong2 ldg_rlx2x64(const unsigned long long* p) {
    ulonglong2 v;
    asm volatile("ld.relaxed.gpu.global.v2.u64 {%0,%1}, [%2];" : "=l"(v.x), "=l"(v.y) : "l"(p) : "memory");
    return v;
}
__device__ __forceinline__ uint32_t ldg_rlx(const uint32_t* p) {
    uint32_t v;
    asm volatile("ld.relaxed.gpu.global.u32 %0, [%1];" : "=r"(v) : "l"(p) : "memory");
    return v;
}
__device__ __forceinline__ void red_add(uint32_t* p, uint32_t v) {
    asm volatile("red.relaxed.gpu.global.add.u32 [%0], %1;" :: "l"(p), "r"(v) : "memory");
}
__device__ __forceinline__ void stg_rlx(uint32_t* p, uint32_t v) {
    asm volatile("st.relaxed.gpu.global.u32 [%0], %1;" :: "l"(p), "r"(v) : "memory");
}
__device__ __forceinline__ void stg_rlx4(uint32_t* p, uint32_t a, uint32_t b, uint32_t c, uint32_t d) {
    asm volatile("st.relaxed.gpu.global.v4.u32 [%0], {%1,%2,%3,%4};" :: "l"(p), "r"(a), "r"(b), "r"(c), "r"(d) : "memory");
}
__device__ __forceinline__ void stg_rlx2x64(unsigned long long* p, unsigned long long a, unsigned long long b) {
    asm volatile("st.relaxed.gpu.global.v2.u64 [%0], {%1,%2};" :: "l"(p), "l"(a), "l"(b) : "memory");
}
__device__ __forceinline__ float lds_f32(uint32_t a) { float v; asm volatile("ld.shared.f32 %0, [%1];" : "=f"(v) : "r"(a) : "memory"); return v; }
__device__ __forceinline__ float4 lds_f32x4(uint32_t a) {
    float4 v; asm volatile("ld.shared.v4.f32 {%0,%1,%2,%3}, [%4];" : "=f"(v.x), "=f"(v.y), "=f"(v.z), "=f"(v.w) : "r"(a) : "memory"); return v;
}
__device__ __forceinline__ uint4 lds_u32x4(uint32_t a) {
    uint4 v; asm volatile("ld.shared.v4.u32 {%0,%1,%2,%3}, [%4];" : "=r"(v.x), "=r"(v.y), "=r"(v.z), "=r"(v.w) : "r"(a) : "memory"); return v;
}
__device__ __forceinline__ void sts_f32(uint32_t a, float v) { asm volatile("st.shared.f32 [%0], %1;" :: "r"(a), "f"(v) : "memory"); }
__device__ __forceinline__ void sts_u32x2(uint32_t a, uint32_t x, uint32_t y) { asm volatile("st.shared.v2.u32 [%0], {%1,%2};" :: "r"(a), "r"(x), "r"(y) : "memory"); }

template <int KSTRIDE>
__device__ __forceinline__ void proj512(float (&out)[4], uint32_t a_addr, uint32_t x_addr) {
    float acc[4][4];
#pragma unroll
    for (int i = 0; i < 4; i++) { acc[i][0] = acc[i][1] = acc[i][2] = acc[i][3] = 0.f; }
#pragma unroll 4
    for (int k2 = 0; k2 < 16; k2++) {
        uint32_t b[4], a0[4], a1[4];
        ldsm4(b, x_addr + k2 * 64);
        ldsm4t(a0, a_addr + (2 * k2) * KSTRIDE);
        ldsm4t(a1, a_addr + (2 * k2 + 1) * KSTRIDE);
        mma16816(acc[(2 * k2) & 3], a0, b[0], b[1]);
        mma16816(acc[(2 * k2 + 1) & 3], a1, b[2], b[3]);
    }
#pragma unroll
    for (int i = 0; i < 4; i++) out[i] = (acc[0][i] + acc[1][i]) + (acc[2][i] + acc[3][i]);
}

__global__ void __launch_bounds__(NTHREADS, 1)
fused_decode_kernel(const __grid_constant__ CUtensorMap mapK, const __grid_constant__ CUtensorMap mapV,
                    const __grid_constant__ CUtensorMap mapWq, const __grid_constant__ CUtensorMap mapWg,
                    const __grid_constant__ CUtensorMap mapWu, const __grid_constant__ CUtensorMap mapWd,
                    const __grid_constant__ CUtensorMap mapWo,
                    const __nv_bfloat16* __restrict__ x, const __nv_bfloat16* __restrict__ gate_w,
                    __nv_bfloat16* __restrict__ out,
                    const uint8_t* __restrict__ wq_raw, const uint8_t* __restrict__ k_raw, const uint8_t* __restrict__ v_raw,
                    const uint8_t* __restrict__ wg_raw, const uint8_t* __restrict__ wu_raw)
{
    if (PF0 && threadIdx.x == 0) {
        if (PF0 & 1) prefetch_l2(wq_raw + (size_t)blockIdx.x * STAGE_BYTES, STAGE_BYTES);
        if (PF0 & 2) prefetch_l2(k_raw + (size_t)blockIdx.x * (4096 * 256), STAGE_BYTES);
        if (PF0 & 4) prefetch_l2(v_raw + (size_t)blockIdx.x * (4096 * 256), STAGE_BYTES);
    }
    if (PFL && threadIdx.x < 128) {
        const uint32_t o = threadIdx.x * PFL_STRIDE;
#pragma unroll
        for (int i = 0; i < STAGE_BYTES / (128 * PFL_STRIDE); i++) {
            if (PFL & 2) asm volatile("prefetch.global.L2 [%0];" :: "l"(k_raw + (size_t)blockIdx.x * (4096 * 256) + o + i * 128 * PFL_STRIDE));
        }
#pragma unroll
        for (int i = 0; i < STAGE_BYTES / (128 * PFL_STRIDE); i++) {
            if (PFL & 1) asm volatile("prefetch.global.L2 [%0];" :: "l"(wq_raw + (size_t)blockIdx.x * STAGE_BYTES + o + i * 128 * PFL_STRIDE));
        }
#pragma unroll
        for (int i = 0; i < STAGE_BYTES / (128 * PFL_STRIDE); i++) {
            if (PFL & 4) asm volatile("prefetch.global.L2 [%0];" :: "l"(v_raw + (size_t)blockIdx.x * (4096 * 256) + o + i * 128 * PFL_STRIDE));
        }
        if ((PFL & 8) && threadIdx.x < 112) {
            asm volatile("prefetch.global.L2 [%0];" :: "l"(wg_raw + ((size_t)blockIdx.x * 112 + threadIdx.x) * 128));
            asm volatile("prefetch.global.L2 [%0];" :: "l"(wu_raw + ((size_t)blockIdx.x * 112 + threadIdx.x) * 128));
        }
    }
    extern __shared__ uint8_t smem_raw[];
    const uint32_t sb = (smem_u32(smem_raw) + 1023u) & ~1023u;
    const int cta = blockIdx.x, tid = threadIdx.x, warp = tid >> 5, lane = tid & 31;
    const bool ffn = cta < NFFN;
    const uint32_t bar_full = sb + OFF_BAR, bar_empty = sb + OFF_BAR + 8 * NSTAGES;

    if (warp == 4) {
        const int nitems = (ffn ? 4 : 2) + 2 * NTILES;
        auto issue = [&](int it, int st) {
            const uint32_t dst = sb + st * STAGE_BYTES, bar = bar_full + 8 * st;
            if (it == 0) {
                mbar_expect_tx(bar, STAGE_BYTES + 4096);
                tma2d(dst, &mapWq, cta * 32, 0, bar);
                tma2d(dst + 16384, &mapWq, cta * 32, 256, bar);
#pragma unroll
                for (int b = 0; b < 4; b++) bulk_load(sb + OFF_XS + b * XS_STRIDE, x + b * 512, 1024, bar);
            } else if (ffn && it == IT_WG) {
                mbar_expect_tx(bar, STAGE_BYTES);
                tma2d(dst,         &mapWg, cta * 16, 0,   bar);
                tma2d(dst + 8192,  &mapWg, cta * 16, 256, bar);
                tma2d(dst + 16384, &mapWu, cta * 16, 0,   bar);
                tma2d(dst + 24576, &mapWu, cta * 16, 256, bar);
            } else if (ffn && it == IT_WD) {
                mbar_expect_tx(bar, 16384);
                tma3d(dst, &mapWd, 0, (cta >> 2) * 64, (cta & 3) * 2, bar);
            } else if (it == nitems - 1) {
                mbar_expect_tx(bar, STAGE_BYTES);
                tma3d(dst, &mapWo, 0, (cta >> 2) * 128, (cta & 3) * 2, bar);
            } else {
                const int j = it - 1 - (ffn ? (it > IT_WG) + (it > IT_WD) : 0);
                mbar_expect_tx(bar, STAGE_BYTES);
                const int row = cta * 4096 + (j >> 1) * TILE;
                tma3d(dst, (j & 1) ? &mapV : &mapK, 0, row, 0, bar);
            }
        };
        if (lane == 0) {
            PROFP(0);
#pragma unroll
            for (int i = 0; i < NSTAGES; i++) { mbar_init(bar_full + 8 * i, 1); mbar_init(bar_empty + 8 * i, 4); }
            asm volatile("fence.mbarrier_init.release.cluster;" ::: "memory");
            asm volatile("fence.proxy.async.shared::cta;" ::: "memory");
            PROFP(16);
#pragma unroll
            for (int i = 0; i < INIT_ITEMS; i++) {
                const int ii = INIT_ORDER == 0 ? i : INIT_ORDER == 1 ? (i < 2 ? 1 - i : i) : (i < 3 ? (i + 1) % 3 : i);
                issue(ii, ii);
            }
        }
        __syncwarp();
        __syncthreads();
        const uint32_t tag32 = *(volatile const uint32_t*)&g_epoch[cta] + 1u;
        const int first_def = nitems - ((ffn && WD_TAIL) ? 2 : 1);
        int st = INIT_ITEMS % NSTAGES, ph = 1, fst = (INIT_ITEMS - WINDOW) % NSTAGES, fph = 0;
        int nl = INIT_ITEMS - WINDOW;
        auto is_kv = [&](int it) { return it > 0 && it < first_def && !(ffn && (it == IT_WG || (!WD_TAIL && it == IT_WD))); };
        auto on_landed = [&]() {
            if (LEADX > 0 && is_kv(nl)) red_add(&g_cnt, 1u);
            if (++fst == NSTAGES) { fst = 0; fph ^= 1; }
            nl++;
            if ((LATE_FLAG || GATE1 == 1) && nl == first_def - 1 - FLAG_LEAD) stg_rlx(g_flag1 + cta, tag32);
        };
        auto wait_landed = [&]() { mbar_wait(bar_full + 8 * fst, fph, 200 + nl); on_landed(); };
        if (lane == 0) {
            const uint32_t cnt0 = (tag32 - 1u) * (uint32_t)(NCTA * 2 * NTILES);
            uint32_t cnt = cnt0;
            int boost = 0;
            for (int it = INIT_ITEMS; it < first_def; it++) {
                const int rem = first_def - it;
                const int win = WINDOW + boost + (rem <= RAMP1) + (rem <= RAMP2) + (rem <= RAMP3);
                const int pos = NCTA * (it - 1 - (ffn ? (it > IT_WG) + (it > IT_WD) : 0));
                while (nl <= it - win) wait_landed();
                if (LEADX > 0 && !boost && is_kv(it)) {
                    int spin = 0;
                    while ((int)(cnt - cnt0) < pos - LEADX) {
                        if (nl < it && mbar_test(bar_full + 8 * fst, fph)) on_landed();
                        cnt = ldg_rlx(&g_cnt);
                        if (++spin > SPIN_LIMIT) SPIN_FAIL(31);
                    }
                }
                if (it >= NSTAGES) mbar_wait(bar_empty + 8 * st, ph, 100 + it);
                issue(it, st);
                if (++st == NSTAGES) { st = 0; ph ^= 1; }
                if (LEADX > 0) {
                    if (BOOSTX < 9999) {
                        const int d = (int)(cnt - cnt0) - pos;
                        boost = (d > -BOOSTX) + (d > -BOOSTX + BOOST2);
                    }
                    cnt = ldg_rlx(&g_cnt);
                }
            }
            if (LATE_FLAG) { while (nl < first_def - 1 - FLAG_LEAD) wait_landed(); }
            else           { while (nl <= first_def - WINDOW) wait_landed(); }
            if (LEADX > 0) {
                for (int i = nl; i < first_def; i++) red_add(&g_cnt, 1u);
            }
        }
        __syncwarp();
        if (LATE_FLAG) {
            const uint32_t* f = GLOBAL_FLAG ? g_flag1 + lane * 4 : g_flag1 + (cta >> 4) * 4 + (lane & 3) * 32;
            int spin = 0;
            while (true) {
                const uint4 v = ldg_rlx4(f);
                const bool ok = v.x == tag32 && v.y == tag32 && v.z == tag32 && v.w == tag32;
                if (__all_sync(0xffffffffu, ok)) break;
                if (++spin > SPIN_LIMIT) SPIN_FAIL(30);
            }
        }
        if (lane == 0) {
            PROFP(19);
            for (int it = first_def; it < nitems; it++) {
                mbar_wait(bar_empty + 8 * st, ph, 100 + it);
                issue(it, st);
                if (++st == NSTAGES) { st = 0; ph ^= 1; }
            }
            PROFP(1);
        }
        return;
    }

    if (warp == 0 && lane < 7) {
        const CUtensorMap* pm = lane == 0 ? &mapWq : lane == 1 ? &mapK : lane == 2 ? &mapV : lane == 3 ? &mapWg : lane == 4 ? &mapWu : lane == 5 ? &mapWd : &mapWo;
        prefetch_map(pm);
    }
    const uint32_t epoch = *(volatile const uint32_t*)&g_epoch[cta];
    if ((PFL & 16) && threadIdx.x < 112) {
        asm volatile("prefetch.global.L2 [%0];" :: "l"(wg_raw + ((size_t)blockIdx.x * 112 + threadIdx.x) * 128));
        asm volatile("prefetch.global.L2 [%0];" :: "l"(wu_raw + ((size_t)blockIdx.x * 112 + threadIdx.x) * 128));
    }
    const uint4 gw0 = __ldg(reinterpret_cast<const uint4*>(gate_w) + lane * 2);
    const uint4 gw1 = __ldg(reinterpret_cast<const uint4*>(gate_w) + lane * 2 + 1);
    __syncthreads();
    const uint32_t tag32 = epoch + 1u, tag16 = tag32 & 0xffffu, tag1 = tag32 & 1u;

    const int r = lane >> 2, c = lane & 3;
    const int bq = cta >> 5, hkv = (cta >> 2) & 7, sq = cta & 3;
    const int kk = cta >> 2, nn = cta & 3;
    int st = 0, ph = 0;
    auto advance = [&]() { if (++st == NSTAGES) { st = 0; ph ^= 1; } };
    auto release = [&]() { __syncwarp(); if (lane == 0) mbar_arrive(bar_empty + 8 * st); };

    const uint32_t xs_lane = sb + OFF_XS + (lane & 3) * XS_STRIDE + (lane >> 3) * 16;

    mbar_wait(bar_full, 0, 1);
    PROF(2);
    if (warp < 2) {
        float d[4];
        const int k = (lane & 7) + 8 * (lane >> 4);
        const int cc = 2 * warp + ((lane >> 3) & 1);
        proj512<1024>(d, sb + k * 64 + ((cc ^ ((lane & 7) >> 1)) << 4), xs_lane);
        const float v0 = (c >= 2) ? d[2] : d[0], v1 = (c >= 2) ? d[3] : d[1];
        uint32_t* dst = g_q + (2 * (c & 1)) * 4096 + cta * 32 + warp * 16 + r + 8 * (c >> 1);
        stg_rlx(dst, (bf16bits(v0) << 16) | tag16);
        stg_rlx(dst + 4096, (bf16bits(v1) << 16) | tag16);
        PROF(11);
    }
    release(); advance();
    {
        const uint4 x0 = lds_u32x4(sb + OFF_XS + warp * XS_STRIDE + lane * 32);
        const uint4 x1 = lds_u32x4(sb + OFF_XS + warp * XS_STRIDE + lane * 32 + 16);
        const uint32_t xv[8] = {x0.x, x0.y, x0.z, x0.w, x1.x, x1.y, x1.z, x1.w};
        const uint32_t wv[8] = {gw0.x, gw0.y, gw0.z, gw0.w, gw1.x, gw1.y, gw1.z, gw1.w};
        float z = 0.f;
#pragma unroll
        for (int i = 0; i < 8; i++) {
            const __nv_bfloat162 p = __hmul2(*reinterpret_cast<const __nv_bfloat162*>(&xv[i]), *reinterpret_cast<const __nv_bfloat162*>(&wv[i]));
            z += __low2float(p) + __high2float(p);
        }
#pragma unroll
        for (int o = 16; o > 0; o >>= 1) z += __shfl_xor_sync(0xffffffffu, z, o);
        z = bf16r(z);
        const float g = bf16r(1.f / (1.f + expf(-z)));
        if (lane == 0) { sts_f32(sb + OFF_GS + warp * 4, g); sts_f32(sb + OFF_GS + 16 + warp * 4, bf16r(1.f - g)); }
    }
    {
        const uint32_t* src = g_q + bq * 4096 + (hkv * 4 + warp) * 128 + lane * 4;
        uint4 v; int it = 0;
        while (true) {
            v = ldg_rlx4(src);
            const bool ok = ((v.x & 0xffffu) == tag16) && ((v.y & 0xffffu) == tag16) && ((v.z & 0xffffu) == tag16) && ((v.w & 0xffffu) == tag16);
            if (__all_sync(0xffffffffu, ok)) break;
            if (++it > SPIN_LIMIT) SPIN_FAIL(21);
        }
        sts_u32x2(sb + OFF_QS + warp * QS_STRIDE + lane * 8, __byte_perm(v.x, v.y, 0x7632), __byte_perm(v.z, v.w, 0x7632));
        PROF(12);
    }
    bar_sync(1, 128);
    PROF(3);
    uint32_t qf[8][2];
#pragma unroll
    for (int k2 = 0; k2 < 4; k2++) {
        uint32_t b[4];
        ldsm4(b, sb + OFF_QS + (lane & 3) * QS_STRIDE + (lane >> 3) * 16 + k2 * 64);
        qf[2 * k2][0] = b[0]; qf[2 * k2][1] = b[1]; qf[2 * k2 + 1][0] = b[2]; qf[2 * k2 + 1][1] = b[3];
    }

    const float sl2 = 0.08838834764831845f * 1.4426950408889634f;
    float O[8][4];
#pragma unroll
    for (int t = 0; t < 8; t++) { O[t][0] = O[t][1] = O[t][2] = O[t][3] = 0.f; }
    float m0 = -INFINITY, m1 = -INFINITY, l0 = 0.f, l1 = 0.f;
    const uint32_t offK = (32 * warp + (lane & 7) + 8 * ((lane >> 3) & 1)) * 128 + (((lane >> 4) ^ (lane & 7)) << 4);
    const uint32_t offV = (32 * warp + (lane & 7) + 8 * (lane >> 4)) * 128 + ((((lane >> 3) & 1) ^ (lane & 7)) << 4);

    float yb[2][4];
#pragma unroll
    for (int i = 0; i < 2; i++) { yb[i][0] = yb[i][1] = yb[i][2] = yb[i][3] = 0.f; }
    const uint32_t offA = ((lane & 7) + 8 * (lane >> 4)) * 128;
    const uint32_t swz0 = ((2 * ((2 * warp) & 3) + ((lane >> 3) & 1)) ^ (lane & 7)) << 4;
    const uint32_t swz1 = ((2 * ((2 * warp + 1) & 3) + ((lane >> 3) & 1)) ^ (lane & 7)) << 4;
    auto down_proj = [&]() {
        uint32_t hb[2][4];
        ldsm4(hb[0], sb + OFF_HS + (lane & 3) * HS_STRIDE + (lane >> 3) * 16);
        ldsm4(hb[1], sb + OFF_HS + (lane & 3) * HS_STRIDE + (lane >> 3) * 16 + 64);
        mbar_wait(bar_full + 8 * st, ph, 6);
        const uint32_t base = sb + st * STAGE_BYTES + (warp >> 1) * 8192 + offA;
#pragma unroll
        for (int ks = 0; ks < 4; ks++) {
            uint32_t a0[4], a1[4];
            ldsm4t(a0, base + ks * 2048 + swz0);
            ldsm4t(a1, base + ks * 2048 + swz1);
            mma16816(yb[0], a0, hb[ks >> 1][2 * (ks & 1)], hb[ks >> 1][2 * (ks & 1) + 1]);
            mma16816(yb[1], a1, hb[ks >> 1][2 * (ks & 1)], hb[ks >> 1][2 * (ks & 1) + 1]);
        }
        release(); advance();
    };
    const int pslot = (bq * 32 + hkv * 4 + warp) * 4 + sq;

#pragma unroll 1
    for (int tile = 0; tile < NTILES; tile++) {
        if (ffn && tile == 1) {
            if (warp >= 2) {
                mbar_wait(bar_full + 8 * st, ph, 2);
                PROFW(2, 13);
                float d[4];
                const int k = (lane & 7) + 8 * (lane >> 4);
                const int cc = (lane >> 3) & 1;
                proj512<512>(d, sb + st * STAGE_BYTES + (warp - 2) * 16384 + k * 32 + ((cc ^ ((lane & 7) >> 2)) << 4), xs_lane);
                const float v0 = bf16r((c >= 2) ? d[2] : d[0]), v1 = bf16r((c >= 2) ? d[3] : d[1]);
                release();
                if (warp == 3) { sts_f32(sb + OFF_UP + lane * 8, v0); sts_f32(sb + OFF_UP + lane * 8 + 4, v1); }
                bar_sync(2, 64);
                if (warp == 2) {
                    const float u0 = lds_f32(sb + OFF_UP + lane * 8), u1 = lds_f32(sb + OFF_UP + lane * 8 + 4);
                    const float h0 = (v0 > 0.f ? v0 : 0.f * v0) * u0, h1 = (v1 > 0.f ? v1 : 0.f * v1) * u1;
                    uint32_t* dst = g_h + (2 * (c & 1)) * 1792 + cta * 16 + r + 8 * (c >> 1);
                    stg_rlx(dst, (bf16bits(h0) << 16) | tag16);
                    stg_rlx(dst + 1792, (bf16bits(h1) << 16) | tag16);
                    PROFW(2, 15);
                }
            } else {
                release();
            }
            advance();
        }
        if (ffn && tile == TILE_H) {
            if (warp < 2) {
                const int b = tid >> 4, f4 = (tid & 15) * 4;
                const uint32_t* src = g_h + b * 1792 + kk * 64 + f4;
                uint4 v; int it = 0;
                while (true) {
                    v = ldg_rlx4(src);
                    const bool ok = ((v.x & 0xffffu) == tag16) && ((v.y & 0xffffu) == tag16) && ((v.z & 0xffffu) == tag16) && ((v.w & 0xffffu) == tag16);
                    if (__all_sync(0xffffffffu, ok)) break;
                    if (++it > SPIN_LIMIT) SPIN_FAIL(22);
                }
                sts_u32x2(sb + OFF_HS + b * HS_STRIDE + f4 * 2, __byte_perm(v.x, v.y, 0x7632), __byte_perm(v.z, v.w, 0x7632));
                PROF(14);
            }
        }
        if (!WD_TAIL && ffn && tile == TILE_WD) {
            bar_sync(1, 128);
            down_proj();
        }
        if (TILE_PRE < NTILES && tile == TILE_PRE) {
            const uint32_t nt = tag1 ^ 1u;
            stg_rlx4(g_part + pslot * 128 + lane * 4, nt, nt, nt, nt);
            if (lane == 0) stg_rlx2x64(g_ml + pslot * 2, tag32 - 1u, tag32 - 1u);
#pragma unroll
            for (int i = 0; i < 2; i++) {
                uint32_t* dst = g_y + ((2 * (c & 1) * 32 + nn * 8 + warp * 2 + i) * 32 + kk) * 16 + r + 8 * (c >> 1);
                stg_rlx(dst, nt);
                stg_rlx(dst + 32 * 32 * 16, nt);
            }
        }
        float s[2][2][4];
        {
            const uint32_t kb = sb + st * STAGE_BYTES;
            mbar_wait(bar_full + 8 * st, ph, 4);
#pragma unroll
            for (int j = 0; j < 2; j++)
#pragma unroll
                for (int h = 0; h < 2; h++) { s[j][h][0] = s[j][h][1] = s[j][h][2] = s[j][h][3] = 0.f; }
#pragma unroll
            for (int ks = 0; ks < 8; ks++) {
#pragma unroll
                for (int j = 0; j < 2; j++) {
                    uint32_t a[4];
                    ldsm4(a, kb + (offK ^ ((ks & 3) << 5)) + (ks >> 2) * 16384 + j * 2048);
                    mma16816(s[j][ks & 1], a, qf[ks][0], qf[ks][1]);
                }
            }
            release(); advance();
        }
        float v[2][4];
#pragma unroll
        for (int j = 0; j < 2; j++)
#pragma unroll
            for (int i = 0; i < 4; i++) v[j][i] = s[j][0][i] + s[j][1][i];
        float mx0 = fmaxf(fmaxf(v[0][0], v[0][2]), fmaxf(v[1][0], v[1][2]));
        float mx1 = fmaxf(fmaxf(v[0][1], v[0][3]), fmaxf(v[1][1], v[1][3]));
#pragma unroll
        for (int o = 4; o < 32; o <<= 1) {
            mx0 = fmaxf(mx0, __shfl_xor_sync(0xffffffffu, mx0, o));
            mx1 = fmaxf(mx1, __shfl_xor_sync(0xffffffffu, mx1, o));
        }
        const float mn0 = fmaxf(m0, mx0 * sl2), mn1 = fmaxf(m1, mx1 * sl2);
        const float al0 = ex2(m0 - mn0), al1 = ex2(m1 - mn1);
        m0 = mn0; m1 = mn1;
        uint32_t pb[2][2];
        float ps0 = 0.f, ps1 = 0.f;
#pragma unroll
        for (int j = 0; j < 2; j++) {
            const float p0 = ex2(fmaf(v[j][0], sl2, -mn0)), p1 = ex2(fmaf(v[j][1], sl2, -mn1));
            const float p2 = ex2(fmaf(v[j][2], sl2, -mn0)), p3 = ex2(fmaf(v[j][3], sl2, -mn1));
            ps0 += p0 + p2; ps1 += p1 + p3;
            pb[j][0] = movm_t(pack_bf16(p0, p1));
            pb[j][1] = movm_t(pack_bf16(p2, p3));
        }
        l0 = l0 * al0 + ps0; l1 = l1 * al1 + ps1;
#pragma unroll
        for (int t = 0; t < 8; t++) { O[t][0] *= al0; O[t][1] *= al1; O[t][2] *= al0; O[t][3] *= al1; }
        {
            const uint32_t vb = sb + st * STAGE_BYTES;
            mbar_wait(bar_full + 8 * st, ph, 5);
            if (GATE1 == 2 && tile == NTILES - 1 && tid == 0) stg_rlx(g_flag2 + cta, tag32);
#pragma unroll
            for (int j = 0; j < 2; j++) {
#pragma unroll
                for (int t = 0; t < 8; t++) {
                    uint32_t a[4];
                    ldsm4t(a, vb + (offV ^ ((t & 3) << 5)) + (t >> 2) * 16384 + j * 2048);
                    mma16816(O[t], a, pb[j][0], pb[j][1]);
                }
            }
            release(); advance();
        }
    }
    PROF(4);

#pragma unroll
    for (int o = 4; o < 32; o <<= 1) {
        l0 += __shfl_xor_sync(0xffffffffu, l0, o);
        l1 += __shfl_xor_sync(0xffffffffu, l1, o);
    }
    {
        const uint32_t so = sb + OFF_SO + ((warp * 4 + 2 * (c & 1)) * SO_STRIDE + 8 * (c >> 1) + r) * 4;
#pragma unroll
        for (int t = 0; t < 8; t++) {
            sts_f32(so + t * 64, (c >= 2) ? O[t][2] : O[t][0]);
            sts_f32(so + t * 64 + SO_STRIDE * 4, (c >= 2) ? O[t][3] : O[t][1]);
        }
        if (lane < 2) {
            const uint32_t sm = sb + OFF_SM + (warp * 4 + 2 * lane) * 4;
            sts_f32(sm, m0); sts_f32(sm + 4, m1); sts_f32(sm + 64, l0); sts_f32(sm + 68, l1);
        }
    }
    bar_sync(1, 128);
    {
        float mw[4], lw[4];
#pragma unroll
        for (int w = 0; w < 4; w++) { mw[w] = lds_f32(sb + OFF_SM + (w * 4 + warp) * 4); lw[w] = lds_f32(sb + OFF_SM + 64 + (w * 4 + warp) * 4); }
        const float M = fmaxf(fmaxf(mw[0], mw[1]), fmaxf(mw[2], mw[3]));
        float4 acc = make_float4(0.f, 0.f, 0.f, 0.f); float L = 0.f;
#pragma unroll
        for (int w = 0; w < 4; w++) {
            const float sc = ex2(mw[w] - M);
            const float4 o = lds_f32x4(sb + OFF_SO + ((w * 4 + warp) * SO_STRIDE + lane * 4) * 4);
            acc.x = fmaf(sc, o.x, acc.x); acc.y = fmaf(sc, o.y, acc.y); acc.z = fmaf(sc, o.z, acc.z); acc.w = fmaf(sc, o.w, acc.w);
            L = fmaf(sc, lw[w], L);
        }
        stg_rlx4(g_part + pslot * 128 + lane * 4,
                 (__float_as_uint(acc.x) & ~1u) | tag1, (__float_as_uint(acc.y) & ~1u) | tag1,
                 (__float_as_uint(acc.z) & ~1u) | tag1, (__float_as_uint(acc.w) & ~1u) | tag1);
        if (lane == 0)
            stg_rlx2x64(g_ml + pslot * 2, ((unsigned long long)__float_as_uint(M) << 32) | tag32, ((unsigned long long)__float_as_uint(L) << 32) | tag32);
    }
    PROF(5);

    float ya[2][2][4];
#pragma unroll
    for (int i = 0; i < 2; i++)
#pragma unroll
        for (int j = 0; j < 2; j++) { ya[i][j][0] = ya[i][j][1] = ya[i][j][2] = ya[i][j][3] = 0.f; }

    {
        const int slot0 = (warp * 32 + kk) * 4;
        uint4 ov[4]; ulonglong2 ml[4];
        int it = 0;
        while (true) {
            bool ok = true;
#pragma unroll
            for (int s = 0; s < 4; s++) {
                ov[s] = ldg_rlx4(g_part + (slot0 + s) * 128 + lane * 4);
                ml[s] = ldg_rlx2x64(g_ml + (slot0 + s) * 2);
            }
#pragma unroll
            for (int s = 0; s < 4; s++) {
                ok = ok && (((ov[s].x ^ tag1) & 1u) == 0) && (((ov[s].y ^ tag1) & 1u) == 0) && (((ov[s].z ^ tag1) & 1u) == 0) && (((ov[s].w ^ tag1) & 1u) == 0);
                ok = ok && ((uint32_t)ml[s].x == tag32) && ((uint32_t)ml[s].y == tag32);
            }
            if (__all_sync(0xffffffffu, ok)) break;
            if (GATE1 && it == 0) {
                const uint32_t* f = (GATE1 == 2 ? g_flag2 : g_flag1) + warp * 32 + (kk >> 2) * 4;
                int spin = 0;
                while (true) {
                    const uint4 v = ldg_rlx4(f);
                    if (v.x == tag32 && v.y == tag32 && v.z == tag32 && v.w == tag32) break;
                    if (++spin > SPIN_LIMIT) SPIN_FAIL(25);
                }
            }
            if (++it > SPIN_LIMIT) SPIN_FAIL(23);
        }
        float Ms[4], M = -INFINITY;
#pragma unroll
        for (int s = 0; s < 4; s++) { Ms[s] = __uint_as_float((uint32_t)(ml[s].x >> 32)); M = fmaxf(M, Ms[s]); }
        float L = 0.f, a0 = 0.f, a1 = 0.f, a2 = 0.f, a3 = 0.f;
#pragma unroll
        for (int s = 0; s < 4; s++) {
            const float w = ex2(Ms[s] - M);
            L  = fmaf(w, __uint_as_float((uint32_t)(ml[s].y >> 32)), L);
            a0 = fmaf(w, __uint_as_float(ov[s].x), a0); a1 = fmaf(w, __uint_as_float(ov[s].y), a1);
            a2 = fmaf(w, __uint_as_float(ov[s].z), a2); a3 = fmaf(w, __uint_as_float(ov[s].w), a3);
        }
        const float inv = 1.f / L;
        sts_u32x2(sb + OFF_OS + warp * QS_STRIDE + lane * 8, pack_bf16(a0 * inv, a1 * inv), pack_bf16(a2 * inv, a3 * inv));
    }
    PROF(7);
    if (WD_TAIL && ffn) down_proj();
    PROF(6);
    bar_sync(1, 128);
    {
        uint32_t ob[4][4];
#pragma unroll
        for (int k2 = 0; k2 < 4; k2++) ldsm4(ob[k2], sb + OFF_OS + (lane & 3) * QS_STRIDE + (lane >> 3) * 16 + k2 * 64);
        mbar_wait(bar_full + 8 * st, ph, 7);
        const uint32_t base = sb + st * STAGE_BYTES + (warp >> 1) * 16384 + offA;
#pragma unroll
        for (int ks = 0; ks < 8; ks++) {
            uint32_t a0[4], a1[4];
            ldsm4t(a0, base + ks * 2048 + swz0);
            ldsm4t(a1, base + ks * 2048 + swz1);
            mma16816(ya[0][ks & 1], a0, ob[ks >> 1][2 * (ks & 1)], ob[ks >> 1][2 * (ks & 1) + 1]);
            mma16816(ya[1][ks & 1], a1, ob[ks >> 1][2 * (ks & 1)], ob[ks >> 1][2 * (ks & 1) + 1]);
        }
        const int b0 = 2 * (c & 1);
        const float g0 = lds_f32(sb + OFF_GS + b0 * 4), g1 = lds_f32(sb + OFF_GS + b0 * 4 + 4);
        const float f0 = lds_f32(sb + OFF_GS + 16 + b0 * 4), f1 = lds_f32(sb + OFF_GS + 16 + b0 * 4 + 4);
#pragma unroll
        for (int i = 0; i < 2; i++) {
            const int e = (c >= 2) ? 2 : 0;
            const float av0 = (e ? ya[i][0][2] + ya[i][1][2] : ya[i][0][0] + ya[i][1][0]);
            const float av1 = (e ? ya[i][0][3] + ya[i][1][3] : ya[i][0][1] + ya[i][1][1]);
            const float bv0 = e ? yb[i][2] : yb[i][0], bv1 = e ? yb[i][3] : yb[i][1];
            const float y0 = fmaf(g0, av0, f0 * bv0), y1 = fmaf(g1, av1, f1 * bv1);
            const int cg = nn * 8 + warp * 2 + i;
            uint32_t* dst = g_y + ((b0 * 32 + cg) * 32 + kk) * 16 + r + 8 * (c >> 1);
            stg_rlx(dst, (__float_as_uint(y0) & ~1u) | tag1);
            stg_rlx(dst + 32 * 32 * 16, (__float_as_uint(y1) & ~1u) | tag1);
        }
    }
    PROF(8);
    if (warp == 0) {
        const uint32_t* src = g_y + (cta * 32 + r) * 16 + c * 4;
        uint4 v[4]; int it = 0;
        while (true) {
            bool ok = true;
#pragma unroll
            for (int i = 0; i < 4; i++) v[i] = ldg_rlx4(src + i * 8 * 16);
#pragma unroll
            for (int i = 0; i < 4; i++)
                ok = ok && (((v[i].x ^ tag1) & 1u) == 0) && (((v[i].y ^ tag1) & 1u) == 0) && (((v[i].z ^ tag1) & 1u) == 0) && (((v[i].w ^ tag1) & 1u) == 0);
            if (__all_sync(0xffffffffu, ok)) break;
            if (++it > SPIN_LIMIT) SPIN_FAIL(24);
        }
        float s0 = 0.f, s1 = 0.f, s2 = 0.f, s3 = 0.f;
#pragma unroll
        for (int i = 0; i < 4; i++) { s0 += __uint_as_float(v[i].x); s1 += __uint_as_float(v[i].y); s2 += __uint_as_float(v[i].z); s3 += __uint_as_float(v[i].w); }
#pragma unroll
        for (int o = 4; o < 32; o <<= 1) {
            s0 += __shfl_xor_sync(0xffffffffu, s0, o); s1 += __shfl_xor_sync(0xffffffffu, s1, o);
            s2 += __shfl_xor_sync(0xffffffffu, s2, o); s3 += __shfl_xor_sync(0xffffffffu, s3, o);
        }
        if (lane < 4) {
            uint2 o2 = make_uint2(pack_bf16(s0, s1), pack_bf16(s2, s3));
            *reinterpret_cast<uint2*>(out + cta * 16 + lane * 4) = o2;
        }
        if (lane == 0) g_epoch[cta] = epoch + 1u;
        PROF(9);
    }
}

typedef CUresult (*EncodeFn)(CUtensorMap*, CUtensorMapDataType, cuuint32_t, void*, const cuuint64_t*, const cuuint64_t*,
                             const cuuint32_t*, const cuuint32_t*, CUtensorMapInterleave, CUtensorMapSwizzle,
                             CUtensorMapL2promotion, CUtensorMapFloatOOBfill);

void make_map(EncodeFn enc, CUtensorMap* m, const void* p, int rank, cuuint64_t d0, cuuint64_t d1, cuuint64_t d2,
              cuuint64_t s1, cuuint64_t s2, cuuint32_t b0, cuuint32_t b1, cuuint32_t b2, CUtensorMapSwizzle sw) {
    cuuint64_t dims[3] = {d0, d1, d2}, strides[2] = {s1, s2};
    cuuint32_t box[3] = {b0, b1, b2}, es[3] = {1, 1, 1};
    enc(m, CU_TENSOR_MAP_DATA_TYPE_BFLOAT16, rank, const_cast<void*>(p), dims, strides, box, es,
        CU_TENSOR_MAP_INTERLEAVE_NONE, sw, CU_TENSOR_MAP_L2_PROMOTION_L2_256B, CU_TENSOR_MAP_FLOAT_OOB_FILL_NONE);
}

}

extern "C" void kernel_launch(void* const* d_in, const int* in_sizes, int n_in, void* d_out, int out_size) {
    (void)in_sizes; (void)n_in; (void)out_size;
    static EncodeFn enc = nullptr;
    if (!enc) {
        void* fn = nullptr;
        cudaDriverEntryPointQueryResult qr;
        cudaGetDriverEntryPoint("cuTensorMapEncodeTiled", &fn, cudaEnableDefault, &qr);
        enc = (EncodeFn)fn;
        cudaFuncSetAttribute(fused_decode_kernel, cudaFuncAttributeMaxDynamicSharedMemorySize, SMEM_BYTES);
    }
    CUtensorMap mK, mV, mWq, mWg, mWu, mWd, mWo;
    make_map(enc, &mK, d_in[1], 3, 64, 4 * 8 * 16384, 2, 256, 128, 64, TILE, 2, CU_TENSOR_MAP_SWIZZLE_128B);
    make_map(enc, &mV, d_in[2], 3, 64, 4 * 8 * 16384, 2, 256, 128, 64, TILE, 2, CU_TENSOR_MAP_SWIZZLE_128B);
    make_map(enc, &mWq, d_in[3], 2, 4096, 512, 1, 8192, 0, 32, 256, 1, CU_TENSOR_MAP_SWIZZLE_64B);
    make_map(enc, &mWg, d_in[6], 2, 1792, 512, 1, 3584, 0, 16, 256, 1, CU_TENSOR_MAP_SWIZZLE_32B);
    make_map(enc, &mWu, d_in[7], 2, 1792, 512, 1, 3584, 0, 16, 256, 1, CU_TENSOR_MAP_SWIZZLE_32B);
    make_map(enc, &mWd, d_in[8], 3, 64, 1792, 8, 1024, 128, 64, 64, 2, CU_TENSOR_MAP_SWIZZLE_128B);
    make_map(enc, &mWo, d_in[4], 3, 64, 4096, 8, 1024, 128, 64, 128, 2, CU_TENSOR_MAP_SWIZZLE_128B);
    fused_decode_kernel<<<NCTA, NTHREADS, SMEM_BYTES>>>(mK, mV, mWq, mWg, mWu, mWd, mWo,
        (const __nv_bfloat16*)d_in[0], (const __nv_bfloat16*)d_in[9], (__nv_bfloat16*)d_out,
        (const uint8_t*)d_in[3], (const uint8_t*)d_in[1], (const uint8_t*)d_in[2], (const uint8_t*)d_in[6], (const uint8_t*)d_in[7]);
}
```

```cpp
#include <cuda_runtime.h>
#include <cuda_bf16.h>
#include <cuda.h>
#include <stdint.h>

namespace {

constexpr int NCTA        = 128;
#define GW 1
#define GTRIG 0
constexpr int NTHREADS    = GW ? 288 : 160;
constexpr int STAGE_BYTES = 32768;
#define NSTAGES 6
#define WINDOW 2
static_assert(WINDOW < NSTAGES, "window must be smaller than the ring");
constexpr int TILE   = 128;
constexpr int NTILES = 4096 / TILE;
constexpr int NFFN   = 112;
#define TILE_WD 32
#define TILE_H 6
#define FLAG_LEAD 0
#define RAMP1 0
#define RAMP2 0
#define RAMP3 0
#define LEADX 512
#define BOOSTX 128
#define BOOST2 9999
#define LATE_FLAG 0
#define INIT_ITEMS 2
#define GLOBAL_FLAG 1
#define GATE1 0
#define PFL 1
#define PFL_STRIDE 256
#define INIT_ORDER 0
#define PF0 0
#define TILE_PRE 99
#define FINAL_PROD 1
#define FIN_SLEEP 0
#define PK1 0
#define PT1 160
#define PK2 0
#define PT2 160
constexpr bool WD_TAIL = TILE_WD >= NTILES;
constexpr int IT_WG = 3;
constexpr int IT_WD = 2 * TILE_WD + 2;
static_assert(WD_TAIL || TILE_H <= TILE_WD, "h must be gathered before W_down is consumed");

constexpr int OFF_BAR = NSTAGES * STAGE_BYTES;
constexpr int OFF_XS  = OFF_BAR + 256;
constexpr int XS_STRIDE = 1040;
constexpr int OFF_QS  = OFF_XS + 4 * XS_STRIDE;
constexpr int QS_STRIDE = 272;
constexpr int OFF_OS  = OFF_QS + 4 * QS_STRIDE;
constexpr int OFF_HS  = OFF_OS + 4 * QS_STRIDE;
constexpr int HS_STRIDE = 144;
constexpr int OFF_SO  = OFF_HS + 4 * HS_STRIDE;
constexpr int SO_STRIDE = 136;
constexpr int OFF_SM  = OFF_SO + 16 * SO_STRIDE * 4;
constexpr int OFF_GS  = OFF_SM + 128;
constexpr int OFF_UP  = OFF_GS + 32;
constexpr int P1_SLOT = 528;
constexpr int OFF_P1  = OFF_UP + 256;
constexpr int OFF_P2  = OFF_P1 + 4 * PK1 * P1_SLOT;
constexpr int SMEM_USED  = OFF_P2 + PK2 * 512;
constexpr int SMEM_BYTES = SMEM_USED + 1024;

__device__ uint32_t g_epoch[NCTA];
__device__ __align__(128) uint32_t g_q[4 * 4096];
__device__ __align__(128) uint32_t g_h[4 * 1792];
__device__ __align__(128) uint32_t g_part[4 * 32 * 4 * 128];
__device__ __align__(128) unsigned long long g_ml[4 * 32 * 4 * 2];
__device__ __align__(128) uint32_t g_y[4 * 32 * 32 * 16];
__device__ __align__(128) uint32_t g_cnt;
__device__ __align__(128) uint32_t g_flag1[NCTA];
__device__ __align__(128) uint32_t g_flag2[NCTA];

#define PROFW(w, i)
#define PROF(i)
#define PROFP(i)

constexpr int SPIN_LIMIT = 1 << 22;
#define SPIN_FAIL(code) __trap()

__device__ __forceinline__ uint32_t smem_u32(const void* p) { return (uint32_t)__cvta_generic_to_shared(p); }
__device__ __forceinline__ void mbar_init(uint32_t bar, uint32_t cnt) {
    asm volatile("mbarrier.init.shared::cta.b64 [%0], %1;" :: "r"(bar), "r"(cnt) : "memory");
}
__device__ __forceinline__ void mbar_expect_tx(uint32_t bar, uint32_t bytes) {
    asm volatile("mbarrier.arrive.expect_tx.shared::cta.b64 _, [%0], %1;" :: "r"(bar), "r"(bytes) : "memory");
}
__device__ __forceinline__ void mbar_arrive(uint32_t bar) {
    asm volatile("mbarrier.arrive.shared::cta.b64 _, [%0];" :: "r"(bar) : "memory");
}
__device__ __forceinline__ bool mbar_try_wait(uint32_t bar, uint32_t parity) {
    uint32_t ok;
    asm volatile("{\n.reg .pred p;\nmbarrier.try_wait.parity.shared::cta.b64 p, [%1], %2;\nselp.u32 %0, 1, 0, p;\n}"
                 : "=r"(ok) : "r"(bar), "r"(parity) : "memory");
    return ok;
}
__device__ __forceinline__ void mbar_wait(uint32_t bar, uint32_t parity, int code = 0) {
    int it = 0;
    while (!mbar_try_wait(bar, parity)) { if (++it > SPIN_LIMIT) SPIN_FAIL(code); }
}
__device__ __forceinline__ bool mbar_test(uint32_t bar, uint32_t parity) {
    uint32_t ok;
    asm volatile("{\n.reg .pred p;\nmbarrier.test_wait.parity.shared::cta.b64 p, [%1], %2;\nselp.u32 %0, 1, 0, p;\n}"
                 : "=r"(ok) : "r"(bar), "r"(parity) : "memory");
    return ok;
}
__device__ __forceinline__ void bulk_load(uint32_t dst, const void* src, uint32_t bytes, uint32_t bar) {
    asm volatile("cp.async.bulk.shared::cluster.global.mbarrier::complete_tx::bytes [%0], [%1], %2, [%3];"
                 :: "r"(dst), "l"(src), "r"(bytes), "r"(bar) : "memory");
}
__device__ __forceinline__ void tma2d(uint32_t dst, const CUtensorMap* tm, int c0, int c1, uint32_t bar) {
    asm volatile("cp.async.bulk.tensor.2d.shared::cluster.global.mbarrier::complete_tx::bytes [%0], [%1, {%3, %4}], [%2];"
                 :: "r"(dst), "l"(tm), "r"(bar), "r"(c0), "r"(c1) : "memory");
}
__device__ __forceinline__ void tma3d(uint32_t dst, const CUtensorMap* tm, int c0, int c1, int c2, uint32_t bar) {
    asm volatile("cp.async.bulk.tensor.3d.shared::cluster.global.mbarrier::complete_tx::bytes [%0], [%1, {%3, %4, %5}], [%2];"
                 :: "r"(dst), "l"(tm), "r"(bar), "r"(c0), "r"(c1), "r"(c2) : "memory");
}
__device__ __forceinline__ void prefetch_l2(const void* p, uint32_t bytes) {
    asm volatile("cp.async.bulk.prefetch.L2.global [%0], %1;" :: "l"(p), "r"(bytes) : "memory");
}
__device__ __forceinline__ void prefetch_map(const CUtensorMap* tm) {
    asm volatile("prefetch.tensormap [%0];" :: "l"(tm) : "memory");
}
__device__ __forceinline__ void ldsm4(uint32_t (&r)[4], uint32_t addr) {
    asm volatile("ldmatrix.sync.aligned.m8n8.x4.shared.b16 {%0,%1,%2,%3}, [%4];"
                 : "=r"(r[0]), "=r"(r[1]), "=r"(r[2]), "=r"(r[3]) : "r"(addr) : "memory");
}
__device__ __forceinline__ void ldsm4t(uint32_t (&r)[4], uint32_t addr) {
    asm volatile("ldmatrix.sync.aligned.m8n8.x4.trans.shared.b16 {%0,%1,%2,%3}, [%4];"
                 : "=r"(r[0]), "=r"(r[1]), "=r"(r[2]), "=r"(r[3]) : "r"(addr) : "memory");
}
__device__ __forceinline__ void mma16816(float (&d)[4], const uint32_t (&a)[4], uint32_t b0, uint32_t b1) {
    asm volatile("mma.sync.aligned.m16n8k16.row.col.f32.bf16.bf16.f32 {%0,%1,%2,%3}, {%4,%5,%6,%7}, {%8,%9}, {%0,%1,%2,%3};"
                 : "+f"(d[0]), "+f"(d[1]), "+f"(d[2]), "+f"(d[3])
                 : "r"(a[0]), "r"(a[1]), "r"(a[2]), "r"(a[3]), "r"(b0), "r"(b1));
}
__device__ __forceinline__ uint32_t movm_t(uint32_t a) {
    uint32_t d;
    asm volatile("movmatrix.sync.aligned.m8n8.trans.b16 %0, %1;" : "=r"(d) : "r"(a));
    return d;
}
__device__ __forceinline__ uint32_t pack_bf16(float lo, float hi) {
    uint32_t d;
    asm("cvt.rn.bf16x2.f32 %0, %1, %2;" : "=r"(d) : "f"(hi), "f"(lo));
    return d;
}
__device__ __forceinline__ float ex2(float x) {
    float y;
    asm("ex2.approx.ftz.f32 %0, %1;" : "=f"(y) : "f"(x));
    return y;
}
__device__ __forceinline__ float bf16r(float x) { return __bfloat162float(__float2bfloat16_rn(x)); }
__device__ __forceinline__ uint32_t bf16bits(float x) { return (uint32_t)__bfloat16_as_ushort(__float2bfloat16_rn(x)); }
__device__ __forceinline__ void bar_sync(int id, int n) { asm volatile("bar.sync %0, %1;" :: "r"(id), "r"(n) : "memory"); }
__device__ __forceinline__ void bar_arrive(int id, int n) { asm volatile("bar.arrive %0, %1;" :: "r"(id), "r"(n) : "memory"); }

__device__ __forceinline__ uint4 ldg_rlx4(const uint32_t* p) {
    uint4 v;
    asm volatile("ld.relaxed.gpu.global.v4.u32 {%0,%1,%2,%3}, [%4];" : "=r"(v.x), "=r"(v.y), "=r"(v.z), "=r"(v.w) : "l"(p) : "memory");
    return v;
}
__device__ __forceinline__ ulonglong2 ldg_rlx2x64(const unsigned long long* p) {
    ulonglong2 v;
    asm volatile("ld.relaxed.gpu.global.v2.u64 {%0,%1}, [%2];" : "=l"(v.x), "=l"(v.y) : "l"(p) : "memory");
    return v;
}
__device__ __forceinline__ uint32_t ldg_rlx(const uint32_t* p) {
    uint32_t v;
    asm volatile("ld.relaxed.gpu.global.u32 %0, [%1];" : "=r"(v) : "l"(p) : "memory");
    return v;
}
__device__ __forceinline__ void ldg_rlx4_if(uint4& v, const uint32_t* p, uint32_t pred) {
    asm volatile("{\n.reg .pred p;\nsetp.ne.u32 p, %5, 0;\n@p ld.relaxed.gpu.global.v4.u32 {%0,%1,%2,%3}, [%4];\n}"
                 : "+r"(v.x), "+r"(v.y), "+r"(v.z), "+r"(v.w) : "l"(p), "r"(pred) : "memory");
}
__device__ __forceinline__ void cpa16_if(uint32_t dst, const void* src, uint32_t pred) {
    asm volatile("{\n.reg .pred p;\nsetp.ne.u32 p, %2, 0;\n@p cp.async.cg.shared.global [%0], [%1], 16;\n}" :: "r"(dst), "l"(src), "r"(pred) : "memory");
}
__device__ __forceinline__ void cpa_commit() { asm volatile("cp.async.commit_group;" ::: "memory"); }
template <int N> __device__ __forceinline__ void cpa_wait() { asm volatile("cp.async.wait_group %0;" :: "n"(N) : "memory"); }
__device__ __forceinline__ uint32_t clk32() { uint32_t t; asm volatile("mov.u32 %0, %clock;" : "=r"(t) :: "memory"); return t; }
__device__ __forceinline__ void red_add(uint32_t* p, uint32_t v) {
    asm volatile("red.relaxed.gpu.global.add.u32 [%0], %1;" :: "l"(p), "r"(v) : "memory");
}
__device__ __forceinline__ void stg_rlx(uint32_t* p, uint32_t v) {
    asm volatile("st.relaxed.gpu.global.u32 [%0], %1;" :: "l"(p), "r"(v) : "memory");
}
__device__ __forceinline__ void stg_rlx4(uint32_t* p, uint32_t a, uint32_t b, uint32_t c, uint32_t d) {
    asm volatile("st.relaxed.gpu.global.v4.u32 [%0], {%1,%2,%3,%4};" :: "l"(p), "r"(a), "r"(b), "r"(c), "r"(d) : "memory");
}
__device__ __forceinline__ void stg_rlx2x64(unsigned long long* p, unsigned long long a, unsigned long long b) {
    asm volatile("st.relaxed.gpu.global.v2.u64 [%0], {%1,%2};" :: "l"(p), "l"(a), "l"(b) : "memory");
}
__device__ __forceinline__ float lds_f32(uint32_t a) { float v; asm volatile("ld.shared.f32 %0, [%1];" : "=f"(v) : "r"(a) : "memory"); return v; }
__device__ __forceinline__ float4 lds_f32x4(uint32_t a) {
    float4 v; asm volatile("ld.shared.v4.f32 {%0,%1,%2,%3}, [%4];" : "=f"(v.x), "=f"(v.y), "=f"(v.z), "=f"(v.w) : "r"(a) : "memory"); return v;
}
__device__ __forceinline__ uint4 lds_u32x4(uint32_t a) {
    uint4 v; asm volatile("ld.shared.v4.u32 {%0,%1,%2,%3}, [%4];" : "=r"(v.x), "=r"(v.y), "=r"(v.z), "=r"(v.w) : "r"(a) : "memory"); return v;
}
__device__ __forceinline__ void sts_f32(uint32_t a, float v) { asm volatile("st.shared.f32 [%0], %1;" :: "r"(a), "f"(v) : "memory"); }
__device__ __forceinline__ void sts_u32x2(uint32_t a, uint32_t x, uint32_t y) { asm volatile("st.shared.v2.u32 [%0], {%1,%2};" :: "r"(a), "r"(x), "r"(y) : "memory"); }

template <int KSTRIDE>
__device__ __forceinline__ void proj512(float (&out)[4], uint32_t a_addr, uint32_t x_addr) {
    float acc[4][4];
#pragma unroll
    for (int i = 0; i < 4; i++) { acc[i][0] = acc[i][1] = acc[i][2] = acc[i][3] = 0.f; }
#pragma unroll 4
    for (int k2 = 0; k2 < 16; k2++) {
        uint32_t b[4], a0[4], a1[4];
        ldsm4(b, x_addr + k2 * 64);
        ldsm4t(a0, a_addr + (2 * k2) * KSTRIDE);
        ldsm4t(a1, a_addr + (2 * k2 + 1) * KSTRIDE);
        mma16816(acc[(2 * k2) & 3], a0, b[0], b[1]);
        mma16816(acc[(2 * k2 + 1) & 3], a1, b[2], b[3]);
    }
#pragma unroll
    for (int i = 0; i < 4; i++) out[i] = (acc[0][i] + acc[1][i]) + (acc[2][i] + acc[3][i]);
}

template <int K>
__device__ __forceinline__ void gather_o_slots(uint32_t sb, int cta, int batch, int lane, uint32_t tag32) {
    const uint32_t tag1 = tag32 & 1u;
    const int slot0 = (batch * 32 + (cta >> 2)) * 4;
    const uint32_t* src = g_part + slot0 * 128 + lane * 4;
    const unsigned long long* srcm = g_ml + slot0 * 2;
    const uint32_t cell = sb + OFF_P1 + batch * (K * P1_SLOT);
    uint4 ov[4]; float Ms[4], Ls[4];
#pragma unroll
    for (int s = 0; s < 4; s++) { ov[s] = make_uint4(0, 0, 0, 0); Ms[s] = Ls[s] = 0.f; }
    uint32_t id[K];
    uint32_t need = 0xFu, nxt = 0, tl = clk32();
    auto issue = [&](int j) {
        const uint32_t rot = ((need * 0x11u) >> nxt) & 0xFu;
        const uint32_t i = (nxt + __ffs(rot) - 1) & 3u;
        id[j] = i; nxt = (i + 1) & 3u;
        if (PT1) { while (clk32() - tl < PT1) { } }
        cpa16_if(cell + j * P1_SLOT + lane * 16, src + i * 128, 1u);
        cpa16_if(cell + j * P1_SLOT + 512, srcm + i * 2, lane == 0);
        cpa_commit();
        if (PT1) tl = clk32();
    };
#pragma unroll
    for (int j = 0; j < K; j++) issue(j);
    int it = 0;
    while (true) {
#pragma unroll
        for (int j = 0; j < K; j++) {
            cpa_wait<K - 1>();
            __syncwarp();
            const uint4 b = lds_u32x4(cell + j * P1_SLOT + lane * 16), m = lds_u32x4(cell + j * P1_SLOT + 512);
            const bool ok = ((((b.x ^ tag1) | (b.y ^ tag1) | (b.z ^ tag1) | (b.w ^ tag1)) & 1u) == 0) && m.x == tag32 && m.z == tag32;
            if (__all_sync(0xffffffffu, ok)) {
#pragma unroll
                for (int s = 0; s < 4; s++)
                    if (id[j] == s) { ov[s] = b; Ms[s] = __uint_as_float(m.y); Ls[s] = __uint_as_float(m.w); }
                need &= ~(1u << id[j]);
                if (need == 0) goto gathered;
            }
            issue(j);
        }
        if (++it > SPIN_LIMIT) SPIN_FAIL(23);
    }
gathered:
    const float M = fmaxf(fmaxf(Ms[0], Ms[1]), fmaxf(Ms[2], Ms[3]));
    float L = 0.f, a0 = 0.f, a1 = 0.f, a2 = 0.f, a3 = 0.f;
#pragma unroll
    for (int s = 0; s < 4; s++) {
        const float w = ex2(Ms[s] - M);
        L  = fmaf(w, Ls[s], L);
        a0 = fmaf(w, __uint_as_float(ov[s].x), a0); a1 = fmaf(w, __uint_as_float(ov[s].y), a1);
        a2 = fmaf(w, __uint_as_float(ov[s].z), a2); a3 = fmaf(w, __uint_as_float(ov[s].w), a3);
    }
    const float inv = 1.f / L;
    sts_u32x2(sb + OFF_OS + batch * QS_STRIDE + lane * 8, pack_bf16(a0 * inv, a1 * inv), pack_bf16(a2 * inv, a3 * inv));
    bar_arrive(4, 256);
    cpa_wait<0>();
}

__device__ __forceinline__ void gather_o(uint32_t sb, int cta, int batch, int lane, uint32_t tag32) {
    const uint32_t tag1 = tag32 & 1u;
    const int slot0 = (batch * 32 + (cta >> 2)) * 4;
    uint4 ov[4]; ulonglong2 ml[4];
    int it = 0;
    while (true) {
        bool ok = true;
#pragma unroll
        for (int s = 0; s < 4; s++) {
            ov[s] = ldg_rlx4(g_part + (slot0 + s) * 128 + lane * 4);
            ml[s] = ldg_rlx2x64(g_ml + (slot0 + s) * 2);
        }
#pragma unroll
        for (int s = 0; s < 4; s++) {
            ok = ok && (((ov[s].x ^ tag1) & 1u) == 0) && (((ov[s].y ^ tag1) & 1u) == 0) && (((ov[s].z ^ tag1) & 1u) == 0) && (((ov[s].w ^ tag1) & 1u) == 0);
            ok = ok && ((uint32_t)ml[s].x == tag32) && ((uint32_t)ml[s].y == tag32);
        }
        if (__all_sync(0xffffffffu, ok)) break;
        if (GATE1 && it == 0) {
            const uint32_t* f = (GATE1 == 2 ? g_flag2 : g_flag1) + batch * 32 + (cta >> 4) * 4;
            int spin = 0;
            while (true) {
                const uint4 v = ldg_rlx4(f);
                if (v.x == tag32 && v.y == tag32 && v.z == tag32 && v.w == tag32) break;
                if (++spin > SPIN_LIMIT) SPIN_FAIL(25);
            }
        }
        if (++it > SPIN_LIMIT) SPIN_FAIL(23);
    }
    float Ms[4], M = -INFINITY;
#pragma unroll
    for (int s = 0; s < 4; s++) { Ms[s] = __uint_as_float((uint32_t)(ml[s].x >> 32)); M = fmaxf(M, Ms[s]); }
    float L = 0.f, a0 = 0.f, a1 = 0.f, a2 = 0.f, a3 = 0.f;
#pragma unroll
    for (int s = 0; s < 4; s++) {
        const float w = ex2(Ms[s] - M);
        L  = fmaf(w, __uint_as_float((uint32_t)(ml[s].y >> 32)), L);
        a0 = fmaf(w, __uint_as_float(ov[s].x), a0); a1 = fmaf(w, __uint_as_float(ov[s].y), a1);
        a2 = fmaf(w, __uint_as_float(ov[s].z), a2); a3 = fmaf(w, __uint_as_float(ov[s].w), a3);
    }
    const float inv = 1.f / L;
    sts_u32x2(sb + OFF_OS + batch * QS_STRIDE + lane * 8, pack_bf16(a0 * inv, a1 * inv), pack_bf16(a2 * inv, a3 * inv));
}

template <int K>
__device__ __forceinline__ void final_reduce_slots(__nv_bfloat16* __restrict__ out, uint32_t sb, int cta, int lane, uint32_t tag32) {
    const uint32_t tag1 = tag32 & 1u;
    const uint32_t* src = g_y + (cta * 32 + (lane >> 2)) * 16 + (lane & 3) * 4;
    const uint32_t cell = sb + OFF_P2 + lane * 16;
    uint4 v[4]; uint32_t id[K];
#pragma unroll
    for (int i = 0; i < 4; i++) v[i] = make_uint4(0, 0, 0, 0);
    uint32_t need = 0xFu, nxt = 0, tl = clk32();
    auto issue = [&](int j) {
        const uint32_t rot = ((need * 0x11u) >> nxt) & 0xFu;
        const uint32_t i = (nxt + __ffs(rot) - 1) & 3u;
        id[j] = need ? i : 4u; nxt = (i + 1) & 3u;
        if (PT2) { while (clk32() - tl < PT2) { } }
        cpa16_if(cell + j * 512, src + i * 128, need);
        cpa_commit();
        if (PT2) tl = clk32();
    };
#pragma unroll
    for (int j = 0; j < K; j++) issue(j);
    int it = 0;
    while (true) {
#pragma unroll
        for (int j = 0; j < K; j++) {
            cpa_wait<K - 1>();
            const uint4 b = lds_u32x4(cell + j * 512);
            const bool ok = (((b.x ^ tag1) | (b.y ^ tag1) | (b.z ^ tag1) | (b.w ^ tag1)) & 1u) == 0;
#pragma unroll
            for (int i = 0; i < 4; i++)
                if (ok && id[j] == i) { v[i] = b; need &= ~(1u << i); }
            if (__all_sync(0xffffffffu, need == 0)) goto reduced;
            issue(j);
        }
        if (++it > SPIN_LIMIT) SPIN_FAIL(24);
    }
reduced:
    float s0 = (__uint_as_float(v[0].x) + __uint_as_float(v[1].x)) + (__uint_as_float(v[2].x) + __uint_as_float(v[3].x));
    float s1 = (__uint_as_float(v[0].y) + __uint_as_float(v[1].y)) + (__uint_as_float(v[2].y) + __uint_as_float(v[3].y));
    float s2 = (__uint_as_float(v[0].z) + __uint_as_float(v[1].z)) + (__uint_as_float(v[2].z) + __uint_as_float(v[3].z));
    float s3 = (__uint_as_float(v[0].w) + __uint_as_float(v[1].w)) + (__uint_as_float(v[2].w) + __uint_as_float(v[3].w));
#pragma unroll
    for (int o = 4; o < 32; o <<= 1) {
        s0 += __shfl_xor_sync(0xffffffffu, s0, o); s1 += __shfl_xor_sync(0xffffffffu, s1, o);
        s2 += __shfl_xor_sync(0xffffffffu, s2, o); s3 += __shfl_xor_sync(0xffffffffu, s3, o);
    }
    if (lane < 4) {
        uint2 o2 = make_uint2(pack_bf16(s0, s1), pack_bf16(s2, s3));
        *reinterpret_cast<uint2*>(out + cta * 16 + lane * 4) = o2;
    }
    if (lane == 0) g_epoch[cta] = tag32;
    cpa_wait<0>();
}

__device__ __forceinline__ void final_reduce(__nv_bfloat16* __restrict__ out, int cta, int lane, uint32_t tag32) {
    const uint32_t tag1 = tag32 & 1u;
    const uint32_t* src = g_y + (cta * 32 + (lane >> 2)) * 16 + (lane & 3) * 4;
    uint4 v[4]; int it = 0;
    while (true) {
        bool ok = true;
#pragma unroll
        for (int i = 0; i < 4; i++) v[i] = ldg_rlx4(src + i * 8 * 16);
#pragma unroll
        for (int i = 0; i < 4; i++)
            ok = ok && (((v[i].x ^ tag1) & 1u) == 0) && (((v[i].y ^ tag1) & 1u) == 0) && (((v[i].z ^ tag1) & 1u) == 0) && (((v[i].w ^ tag1) & 1u) == 0);
        if (__all_sync(0xffffffffu, ok)) break;
        if (++it > SPIN_LIMIT) SPIN_FAIL(24);
        if (FIN_SLEEP) __nanosleep(FIN_SLEEP);
    }
    float s0 = 0.f, s1 = 0.f, s2 = 0.f, s3 = 0.f;
#pragma unroll
    for (int i = 0; i < 4; i++) { s0 += __uint_as_float(v[i].x); s1 += __uint_as_float(v[i].y); s2 += __uint_as_float(v[i].z); s3 += __uint_as_float(v[i].w); }
#pragma unroll
    for (int o = 4; o < 32; o <<= 1) {
        s0 += __shfl_xor_sync(0xffffffffu, s0, o); s1 += __shfl_xor_sync(0xffffffffu, s1, o);
        s2 += __shfl_xor_sync(0xffffffffu, s2, o); s3 += __shfl_xor_sync(0xffffffffu, s3, o);
    }
    if (lane < 4) {
        uint2 o2 = make_uint2(pack_bf16(s0, s1), pack_bf16(s2, s3));
        *reinterpret_cast<uint2*>(out + cta * 16 + lane * 4) = o2;
    }
    if (lane == 0) g_epoch[cta] = tag32;
}

__global__ void __launch_bounds__(NTHREADS, 1)
fused_decode_kernel(const __grid_constant__ CUtensorMap mapK, const __grid_constant__ CUtensorMap mapV,
                    const __grid_constant__ CUtensorMap mapWq, const __grid_constant__ CUtensorMap mapWg,
                    const __grid_constant__ CUtensorMap mapWu, const __grid_constant__ CUtensorMap mapWd,
                    const __grid_constant__ CUtensorMap mapWo,
                    const __nv_bfloat16* __restrict__ x, const __nv_bfloat16* __restrict__ gate_w,
                    __nv_bfloat16* __restrict__ out,
                    const uint8_t* __restrict__ wq_raw, const uint8_t* __restrict__ k_raw, const uint8_t* __restrict__ v_raw,
                    const uint8_t* __restrict__ wg_raw, const uint8_t* __restrict__ wu_raw)
{
    if (PF0 && threadIdx.x == 0) {
        if (PF0 & 1) prefetch_l2(wq_raw + (size_t)blockIdx.x * STAGE_BYTES, STAGE_BYTES);
        if (PF0 & 2) prefetch_l2(k_raw + (size_t)blockIdx.x * (4096 * 256), STAGE_BYTES);
        if (PF0 & 4) prefetch_l2(v_raw + (size_t)blockIdx.x * (4096 * 256), STAGE_BYTES);
    }
    if (PFL && threadIdx.x < 128) {
        const uint32_t o = threadIdx.x * PFL_STRIDE;
#pragma unroll
        for (int i = 0; i < STAGE_BYTES / (128 * PFL_STRIDE); i++) {
            if (PFL & 2) asm volatile("prefetch.global.L2 [%0];" :: "l"(k_raw + (size_t)blockIdx.x * (4096 * 256) + o + i * 128 * PFL_STRIDE));
        }
#pragma unroll
        for (int i = 0; i < STAGE_BYTES / (128 * PFL_STRIDE); i++) {
            if (PFL & 1) asm volatile("prefetch.global.L2 [%0];" :: "l"(wq_raw + (size_t)blockIdx.x * STAGE_BYTES + o + i * 128 * PFL_STRIDE));
        }
#pragma unroll
        for (int i = 0; i < STAGE_BYTES / (128 * PFL_STRIDE); i++) {
            if (PFL & 4) asm volatile("prefetch.global.L2 [%0];" :: "l"(v_raw + (size_t)blockIdx.x * (4096 * 256) + o + i * 128 * PFL_STRIDE));
        }
        if ((PFL & 8) && threadIdx.x < 112) {
            asm volatile("prefetch.global.L2 [%0];" :: "l"(wg_raw + ((size_t)blockIdx.x * 112 + threadIdx.x) * 128));
            asm volatile("prefetch.global.L2 [%0];" :: "l"(wu_raw + ((size_t)blockIdx.x * 112 + threadIdx.x) * 128));
        }
    }
    extern __shared__ uint8_t smem_raw[];
    const uint32_t sb = (smem_u32(smem_raw) + 1023u) & ~1023u;
    const int cta = blockIdx.x, tid = threadIdx.x, warp = tid >> 5, lane = tid & 31;
    const bool ffn = cta < NFFN;
    const uint32_t bar_full = sb + OFF_BAR, bar_empty = sb + OFF_BAR + 8 * NSTAGES, bar_go = sb + OFF_BAR + 16 * NSTAGES;

    if (warp == 4) {
        const int nitems = (ffn ? 4 : 2) + 2 * NTILES;
        auto issue = [&](int it, int st) {
            const uint32_t dst = sb + st * STAGE_BYTES, bar = bar_full + 8 * st;
            if (it == 0) {
                mbar_expect_tx(bar, STAGE_BYTES + 4096);
                tma2d(dst, &mapWq, cta * 32, 0, bar);
                tma2d(dst + 16384, &mapWq, cta * 32, 256, bar);
#pragma unroll
                for (int b = 0; b < 4; b++) bulk_load(sb + OFF_XS + b * XS_STRIDE, x + b * 512, 1024, bar);
            } else if (ffn && it == IT_WG) {
                mbar_expect_tx(bar, STAGE_BYTES);
                tma2d(dst,         &mapWg, cta * 16, 0,   bar);
                tma2d(dst + 8192,  &mapWg, cta * 16, 256, bar);
                tma2d(dst + 16384, &mapWu, cta * 16, 0,   bar);
                tma2d(dst + 24576, &mapWu, cta * 16, 256, bar);
            } else if (ffn && it == IT_WD) {
                mbar_expect_tx(bar, 16384);
                tma3d(dst, &mapWd, 0, (cta >> 2) * 64, (cta & 3) * 2, bar);
            } else if (it == nitems - 1) {
                mbar_expect_tx(bar, STAGE_BYTES);
                tma3d(dst, &mapWo, 0, (cta >> 2) * 128, (cta & 3) * 2, bar);
            } else {
                const int j = it - 1 - (ffn ? (it > IT_WG) + (it > IT_WD) : 0);
                mbar_expect_tx(bar, STAGE_BYTES);
                const int row = cta * 4096 + (j >> 1) * TILE;
                tma3d(dst, (j & 1) ? &mapV : &mapK, 0, row, 0, bar);
            }
        };
        if (lane == 0) {
            PROFP(0);
#pragma unroll
            for (int i = 0; i < NSTAGES; i++) { mbar_init(bar_full + 8 * i, 1); mbar_init(bar_empty + 8 * i, 4); }
            if (GW) mbar_init(bar_go, 1);
            asm volatile("fence.mbarrier_init.release.cluster;" ::: "memory");
            asm volatile("fence.proxy.async.shared::cta;" ::: "memory");
            PROFP(16);
#pragma unroll
            for (int i = 0; i < INIT_ITEMS; i++) {
                const int ii = INIT_ORDER == 0 ? i : INIT_ORDER == 1 ? (i < 2 ? 1 - i : i) : (i < 3 ? (i + 1) % 3 : i);
                issue(ii, ii);
            }
        }
        __syncwarp();
        __syncthreads();
        const uint32_t tag32 = *(volatile const uint32_t*)&g_epoch[cta] + 1u;
        const int first_def = nitems - ((ffn && WD_TAIL) ? 2 : 1);
        int st = INIT_ITEMS % NSTAGES, ph = 1, fst = (INIT_ITEMS - WINDOW) % NSTAGES, fph = 0;
        int nl = INIT_ITEMS - WINDOW;
        auto is_kv = [&](int it) { return it > 0 && it < first_def && !(ffn && (it == IT_WG || (!WD_TAIL && it == IT_WD))); };
        auto on_landed = [&]() {
            if (LEADX > 0 && is_kv(nl)) red_add(&g_cnt, 1u);
            if (++fst == NSTAGES) { fst = 0; fph ^= 1; }
            nl++;
            if ((LATE_FLAG || GATE1 == 1) && nl == first_def - 1 - FLAG_LEAD) stg_rlx(g_flag1 + cta, tag32);
        };
        auto wait_landed = [&]() { mbar_wait(bar_full + 8 * fst, fph, 200 + nl); on_landed(); };
        if (lane == 0) {
            const uint32_t cnt0 = (tag32 - 1u) * (uint32_t)(NCTA * 2 * NTILES);
            uint32_t cnt = cnt0;
            int boost = 0;
            for (int it = INIT_ITEMS; it < first_def; it++) {
                const int rem = first_def - it;
                const int win = WINDOW + boost + (rem <= RAMP1) + (rem <= RAMP2) + (rem <= RAMP3);
                const int pos = NCTA * (it - 1 - (ffn ? (it > IT_WG) + (it > IT_WD) : 0));
                while (nl <= it - win) wait_landed();
                if (LEADX > 0 && !boost && is_kv(it)) {
                    int spin = 0;
                    while ((int)(cnt - cnt0) < pos - LEADX) {
                        if (nl < it && mbar_test(bar_full + 8 * fst, fph)) on_landed();
                        cnt = ldg_rlx(&g_cnt);
                        if (++spin > SPIN_LIMIT) SPIN_FAIL(31);
                    }
                }
                if (it >= NSTAGES) mbar_wait(bar_empty + 8 * st, ph, 100 + it);
                issue(it, st);
                if (GW && GTRIG > 0 && rem == GTRIG) mbar_arrive(bar_go);
                if (++st == NSTAGES) { st = 0; ph ^= 1; }
                if (LEADX > 0) {
                    if (BOOSTX < 9999) {
                        const int d = (int)(cnt - cnt0) - pos;
                        boost = (d > -BOOSTX) + (d > -BOOSTX + BOOST2);
                    }
                    cnt = ldg_rlx(&g_cnt);
                }
            }
            if (LATE_FLAG) { while (nl < first_def - 1 - FLAG_LEAD) wait_landed(); }
            else           { while (nl <= first_def - WINDOW) wait_landed(); }
            if (GW && GTRIG == 0) mbar_arrive(bar_go);
            if (LEADX > 0) {
                for (int i = nl; i < first_def; i++) red_add(&g_cnt, 1u);
            }
        }
        __syncwarp();
        if (LATE_FLAG) {
            const uint32_t* f = GLOBAL_FLAG ? g_flag1 + lane * 4 : g_flag1 + (cta >> 4) * 4 + (lane & 3) * 32;
            int spin = 0;
            while (true) {
                const uint4 v = ldg_rlx4(f);
                const bool ok = v.x == tag32 && v.y == tag32 && v.z == tag32 && v.w == tag32;
                if (__all_sync(0xffffffffu, ok)) break;
                if (++spin > SPIN_LIMIT) SPIN_FAIL(30);
            }
        }
        if (lane == 0) {
            PROFP(19);
            for (int it = first_def; it < nitems; it++) {
                mbar_wait(bar_empty + 8 * st, ph, 100 + it);
                issue(it, st);
                if (++st == NSTAGES) { st = 0; ph ^= 1; }
            }
            PROFP(1);
        }
        if (FINAL_PROD) {
            __syncwarp();
            if (PK2) final_reduce_slots<PK2 ? PK2 : 1>(out, sb, cta, lane, tag32);
            else     final_reduce(out, cta, lane, tag32);
        }
        return;
    }

    if (GW && warp > 4) {
        const uint32_t t32 = *(volatile const uint32_t*)&g_epoch[cta] + 1u;
        __syncthreads();
        mbar_wait(bar_go, 0, 8);
        if (PK1) {
            gather_o_slots<PK1 ? PK1 : 1>(sb, cta, warp - 5, lane, t32);
            PROFW(5, 7);
        } else {
            gather_o(sb, cta, warp - 5, lane, t32);
            PROFW(5, 7);
            bar_arrive(4, 256);
        }
        return;
    }

    if (warp == 0 && lane < 7) {
        const CUtensorMap* pm = lane == 0 ? &mapWq : lane == 1 ? &mapK : lane == 2 ? &mapV : lane == 3 ? &mapWg : lane == 4 ? &mapWu : lane == 5 ? &mapWd : &mapWo;
        prefetch_map(pm);
    }
    const uint32_t epoch = *(volatile const uint32_t*)&g_epoch[cta];
    if ((PFL & 16) && threadIdx.x < 112) {
        asm volatile("prefetch.global.L2 [%0];" :: "l"(wg_raw + ((size_t)blockIdx.x * 112 + threadIdx.x) * 128));
        asm volatile("prefetch.global.L2 [%0];" :: "l"(wu_raw + ((size_t)blockIdx.x * 112 + threadIdx.x) * 128));
    }
    const uint4 gw0 = __ldg(reinterpret_cast<const uint4*>(gate_w) + lane * 2);
    const uint4 gw1 = __ldg(reinterpret_cast<const uint4*>(gate_w) + lane * 2 + 1);
    __syncthreads();
    const uint32_t tag32 = epoch + 1u, tag16 = tag32 & 0xffffu, tag1 = tag32 & 1u;

    const int r = lane >> 2, c = lane & 3;
    const int bq = cta >> 5, hkv = (cta >> 2) & 7, sq = cta & 3;
    const int kk = cta >> 2, nn = cta & 3;
    int st = 0, ph = 0;
    auto advance = [&]() { if (++st == NSTAGES) { st = 0; ph ^= 1; } };
    auto release = [&]() { __syncwarp(); if (lane == 0) mbar_arrive(bar_empty + 8 * st); };

    const uint32_t xs_lane = sb + OFF_XS + (lane & 3) * XS_STRIDE + (lane >> 3) * 16;

    mbar_wait(bar_full, 0, 1);
    PROF(2);
    if (warp < 2) {
        float d[4];
        const int k = (lane & 7) + 8 * (lane >> 4);
        const int cc = 2 * warp + ((lane >> 3) & 1);
        proj512<1024>(d, sb + k * 64 + ((cc ^ ((lane & 7) >> 1)) << 4), xs_lane);
        const float v0 = (c >= 2) ? d[2] : d[0], v1 = (c >= 2) ? d[3] : d[1];
        uint32_t* dst = g_q + (2 * (c & 1)) * 4096 + cta * 32 + warp * 16 + r + 8 * (c >> 1);
        stg_rlx(dst, (bf16bits(v0) << 16) | tag16);
        stg_rlx(dst + 4096, (bf16bits(v1) << 16) | tag16);
        PROF(11);
    }
    release(); advance();
    {
        const uint4 x0 = lds_u32x4(sb + OFF_XS + warp * XS_STRIDE + lane * 32);
        const uint4 x1 = lds_u32x4(sb + OFF_XS + warp * XS_STRIDE + lane * 32 + 16);
        const uint32_t xv[8] = {x0.x, x0.y, x0.z, x0.w, x1.x, x1.y, x1.z, x1.w};
        const uint32_t wv[8] = {gw0.x, gw0.y, gw0.z, gw0.w, gw1.x, gw1.y, gw1.z, gw1.w};
        float z = 0.f;
#pragma unroll
        for (int i = 0; i < 8; i++) {
            const __nv_bfloat162 p = __hmul2(*reinterpret_cast<const __nv_bfloat162*>(&xv[i]), *reinterpret_cast<const __nv_bfloat162*>(&wv[i]));
            z += __low2float(p) + __high2float(p);
        }
#pragma unroll
        for (int o = 16; o > 0; o >>= 1) z += __shfl_xor_sync(0xffffffffu, z, o);
        z = bf16r(z);
        const float g = bf16r(1.f / (1.f + expf(-z)));
        if (lane == 0) { sts_f32(sb + OFF_GS + warp * 4, g); sts_f32(sb + OFF_GS + 16 + warp * 4, bf16r(1.f - g)); }
    }
    {
        const uint32_t* src = g_q + bq * 4096 + (hkv * 4 + warp) * 128 + lane * 4;
        uint4 v; int it = 0;
        while (true) {
            v = ldg_rlx4(src);
            const bool ok = ((v.x & 0xffffu) == tag16) && ((v.y & 0xffffu) == tag16) && ((v.z & 0xffffu) == tag16) && ((v.w & 0xffffu) == tag16);
            if (__all_sync(0xffffffffu, ok)) break;
            if (++it > SPIN_LIMIT) SPIN_FAIL(21);
        }
        sts_u32x2(sb + OFF_QS + warp * QS_STRIDE + lane * 8, __byte_perm(v.x, v.y, 0x7632), __byte_perm(v.z, v.w, 0x7632));
        PROF(12);
    }
    bar_sync(1, 128);
    PROF(3);
    uint32_t qf[8][2];
#pragma unroll
    for (int k2 = 0; k2 < 4; k2++) {
        uint32_t b[4];
        ldsm4(b, sb + OFF_QS + (lane & 3) * QS_STRIDE + (lane >> 3) * 16 + k2 * 64);
        qf[2 * k2][0] = b[0]; qf[2 * k2][1] = b[1]; qf[2 * k2 + 1][0] = b[2]; qf[2 * k2 + 1][1] = b[3];
    }

    const float sl2 = 0.08838834764831845f * 1.4426950408889634f;
    float O[8][4];
#pragma unroll
    for (int t = 0; t < 8; t++) { O[t][0] = O[t][1] = O[t][2] = O[t][3] = 0.f; }
    float m0 = -INFINITY, m1 = -INFINITY, l0 = 0.f, l1 = 0.f;
    const uint32_t offK = (32 * warp + (lane & 7) + 8 * ((lane >> 3) & 1)) * 128 + (((lane >> 4) ^ (lane & 7)) << 4);
    const uint32_t offV = (32 * warp + (lane & 7) + 8 * (lane >> 4)) * 128 + ((((lane >> 3) & 1) ^ (lane & 7)) << 4);

    float yb[2][4];
#pragma unroll
    for (int i = 0; i < 2; i++) { yb[i][0] = yb[i][1] = yb[i][2] = yb[i][3] = 0.f; }
    const uint32_t offA = ((lane & 7) + 8 * (lane >> 4)) * 128;
    const uint32_t swz0 = ((2 * ((2 * warp) & 3) + ((lane >> 3) & 1)) ^ (lane & 7)) << 4;
    const uint32_t swz1 = ((2 * ((2 * warp + 1) & 3) + ((lane >> 3) & 1)) ^ (lane & 7)) << 4;
    auto down_proj = [&]() {
        uint32_t hb[2][4];
        ldsm4(hb[0], sb + OFF_HS + (lane & 3) * HS_STRIDE + (lane >> 3) * 16);
        ldsm4(hb[1], sb + OFF_HS + (lane & 3) * HS_STRIDE + (lane >> 3) * 16 + 64);
        mbar_wait(bar_full + 8 * st, ph, 6);
        const uint32_t base = sb + st * STAGE_BYTES + (warp >> 1) * 8192 + offA;
#pragma unroll
        for (int ks = 0; ks < 4; ks++) {
            uint32_t a0[4], a1[4];
            ldsm4t(a0, base + ks * 2048 + swz0);
            ldsm4t(a1, base + ks * 2048 + swz1);
            mma16816(yb[0], a0, hb[ks >> 1][2 * (ks & 1)], hb[ks >> 1][2 * (ks & 1) + 1]);
            mma16816(yb[1], a1, hb[ks >> 1][2 * (ks & 1)], hb[ks >> 1][2 * (ks & 1) + 1]);
        }
        release(); advance();
    };
    const int pslot = (bq * 32 + hkv * 4 + warp) * 4 + sq;

#pragma unroll 1
    for (int tile = 0; tile < NTILES; tile++) {
        if (ffn && tile == 1) {
            if (warp >= 2) {
                mbar_wait(bar_full + 8 * st, ph, 2);
                PROFW(2, 13);
                float d[4];
                const int k = (lane & 7) + 8 * (lane >> 4);
                const int cc = (lane >> 3) & 1;
                proj512<512>(d, sb + st * STAGE_BYTES + (warp - 2) * 16384 + k * 32 + ((cc ^ ((lane & 7) >> 2)) << 4), xs_lane);
                const float v0 = bf16r((c >= 2) ? d[2] : d[0]), v1 = bf16r((c >= 2) ? d[3] : d[1]);
                release();
                if (warp == 3) { sts_f32(sb + OFF_UP + lane * 8, v0); sts_f32(sb + OFF_UP + lane * 8 + 4, v1); }
                bar_sync(2, 64);
                if (warp == 2) {
                    const float u0 = lds_f32(sb + OFF_UP + lane * 8), u1 = lds_f32(sb + OFF_UP + lane * 8 + 4);
                    const float h0 = (v0 > 0.f ? v0 : 0.f * v0) * u0, h1 = (v1 > 0.f ? v1 : 0.f * v1) * u1;
                    uint32_t* dst = g_h + (2 * (c & 1)) * 1792 + cta * 16 + r + 8 * (c >> 1);
                    stg_rlx(dst, (bf16bits(h0) << 16) | tag16);
                    stg_rlx(dst + 1792, (bf16bits(h1) << 16) | tag16);
                    PROFW(2, 15);
                }
            } else {
                release();
            }
            advance();
        }
        if (ffn && tile == TILE_H) {
            if (warp < 2) {
                const int b = tid >> 4, f4 = (tid & 15) * 4;
                const uint32_t* src = g_h + b * 1792 + kk * 64 + f4;
                uint4 v; int it = 0;
                while (true) {
                    v = ldg_rlx4(src);
                    const bool ok = ((v.x & 0xffffu) == tag16) && ((v.y & 0xffffu) == tag16) && ((v.z & 0xffffu) == tag16) && ((v.w & 0xffffu) == tag16);
                    if (__all_sync(0xffffffffu, ok)) break;
                    if (++it > SPIN_LIMIT) SPIN_FAIL(22);
                }
                sts_u32x2(sb + OFF_HS + b * HS_STRIDE + f4 * 2, __byte_perm(v.x, v.y, 0x7632), __byte_perm(v.z, v.w, 0x7632));
                PROF(14);
            }
        }
        if (!WD_TAIL && ffn && tile == TILE_WD) {
            bar_sync(1, 128);
            down_proj();
        }
        if (TILE_PRE < NTILES && tile == TILE_PRE) {
            const uint32_t nt = tag1 ^ 1u;
            stg_rlx4(g_part + pslot * 128 + lane * 4, nt, nt, nt, nt);
            if (lane == 0) stg_rlx2x64(g_ml + pslot * 2, tag32 - 1u, tag32 - 1u);
#pragma unroll
            for (int i = 0; i < 2; i++) {
                uint32_t* dst = g_y + ((2 * (c & 1) * 32 + nn * 8 + warp * 2 + i) * 32 + kk) * 16 + r + 8 * (c >> 1);
                stg_rlx(dst, nt);
                stg_rlx(dst + 32 * 32 * 16, nt);
            }
        }
        float s[2][2][4];
        {
            const uint32_t kb = sb + st * STAGE_BYTES;
            mbar_wait(bar_full + 8 * st, ph, 4);
#pragma unroll
            for (int j = 0; j < 2; j++)
#pragma unroll
                for (int h = 0; h < 2; h++) { s[j][h][0] = s[j][h][1] = s[j][h][2] = s[j][h][3] = 0.f; }
#pragma unroll
            for (int ks = 0; ks < 8; ks++) {
#pragma unroll
                for (int j = 0; j < 2; j++) {
                    uint32_t a[4];
                    ldsm4(a, kb + (offK ^ ((ks & 3) << 5)) + (ks >> 2) * 16384 + j * 2048);
                    mma16816(s[j][ks & 1], a, qf[ks][0], qf[ks][1]);
                }
            }
            release(); advance();
        }
        float v[2][4];
#pragma unroll
        for (int j = 0; j < 2; j++)
#pragma unroll
            for (int i = 0; i < 4; i++) v[j][i] = s[j][0][i] + s[j][1][i];
        float mx0 = fmaxf(fmaxf(v[0][0], v[0][2]), fmaxf(v[1][0], v[1][2]));
        float mx1 = fmaxf(fmaxf(v[0][1], v[0][3]), fmaxf(v[1][1], v[1][3]));
#pragma unroll
        for (int o = 4; o < 32; o <<= 1) {
            mx0 = fmaxf(mx0, __shfl_xor_sync(0xffffffffu, mx0, o));
            mx1 = fmaxf(mx1, __shfl_xor_sync(0xffffffffu, mx1, o));
        }
        const float mn0 = fmaxf(m0, mx0 * sl2), mn1 = fmaxf(m1, mx1 * sl2);
        const float al0 = ex2(m0 - mn0), al1 = ex2(m1 - mn1);
        m0 = mn0; m1 = mn1;
        uint32_t pb[2][2];
        float ps0 = 0.f, ps1 = 0.f;
#pragma unroll
        for (int j = 0; j < 2; j++) {
            const float p0 = ex2(fmaf(v[j][0], sl2, -mn0)), p1 = ex2(fmaf(v[j][1], sl2, -mn1));
            const float p2 = ex2(fmaf(v[j][2], sl2, -mn0)), p3 = ex2(fmaf(v[j][3], sl2, -mn1));
            ps0 += p0 + p2; ps1 += p1 + p3;
            pb[j][0] = movm_t(pack_bf16(p0, p1));
            pb[j][1] = movm_t(pack_bf16(p2, p3));
        }
        l0 = l0 * al0 + ps0; l1 = l1 * al1 + ps1;
#pragma unroll
        for (int t = 0; t < 8; t++) { O[t][0] *= al0; O[t][1] *= al1; O[t][2] *= al0; O[t][3] *= al1; }
        {
            const uint32_t vb = sb + st * STAGE_BYTES;
            mbar_wait(bar_full + 8 * st, ph, 5);
            if (GATE1 == 2 && tile == NTILES - 1 && tid == 0) stg_rlx(g_flag2 + cta, tag32);
#pragma unroll
            for (int j = 0; j < 2; j++) {
#pragma unroll
                for (int t = 0; t < 8; t++) {
                    uint32_t a[4];
                    ldsm4t(a, vb + (offV ^ ((t & 3) << 5)) + (t >> 2) * 16384 + j * 2048);
                    mma16816(O[t], a, pb[j][0], pb[j][1]);
                }
            }
            release(); advance();
        }
    }
    PROF(4);

#pragma unroll
    for (int o = 4; o < 32; o <<= 1) {
        l0 += __shfl_xor_sync(0xffffffffu, l0, o);
        l1 += __shfl_xor_sync(0xffffffffu, l1, o);
    }
    {
        const uint32_t so = sb + OFF_SO + ((warp * 4 + 2 * (c & 1)) * SO_STRIDE + 8 * (c >> 1) + r) * 4;
#pragma unroll
        for (int t = 0; t < 8; t++) {
            sts_f32(so + t * 64, (c >= 2) ? O[t][2] : O[t][0]);
            sts_f32(so + t * 64 + SO_STRIDE * 4, (c >= 2) ? O[t][3] : O[t][1]);
        }
        if (lane < 2) {
            const uint32_t sm = sb + OFF_SM + (warp * 4 + 2 * lane) * 4;
            sts_f32(sm, m0); sts_f32(sm + 4, m1); sts_f32(sm + 64, l0); sts_f32(sm + 68, l1);
        }
    }
    bar_sync(1, 128);
    {
        float mw[4], lw[4];
#pragma unroll
        for (int w = 0; w < 4; w++) { mw[w] = lds_f32(sb + OFF_SM + (w * 4 + warp) * 4); lw[w] = lds_f32(sb + OFF_SM + 64 + (w * 4 + warp) * 4); }
        const float M = fmaxf(fmaxf(mw[0], mw[1]), fmaxf(mw[2], mw[3]));
        float4 acc = make_float4(0.f, 0.f, 0.f, 0.f); float L = 0.f;
#pragma unroll
        for (int w = 0; w < 4; w++) {
            const float sc = ex2(mw[w] - M);
            const float4 o = lds_f32x4(sb + OFF_SO + ((w * 4 + warp) * SO_STRIDE + lane * 4) * 4);
            acc.x = fmaf(sc, o.x, acc.x); acc.y = fmaf(sc, o.y, acc.y); acc.z = fmaf(sc, o.z, acc.z); acc.w = fmaf(sc, o.w, acc.w);
            L = fmaf(sc, lw[w], L);
        }
        stg_rlx4(g_part + pslot * 128 + lane * 4,
                 (__float_as_uint(acc.x) & ~1u) | tag1, (__float_as_uint(acc.y) & ~1u) | tag1,
                 (__float_as_uint(acc.z) & ~1u) | tag1, (__float_as_uint(acc.w) & ~1u) | tag1);
        if (lane == 0)
            stg_rlx2x64(g_ml + pslot * 2, ((unsigned long long)__float_as_uint(M) << 32) | tag32, ((unsigned long long)__float_as_uint(L) << 32) | tag32);
    }
    PROF(5);

    if (!GW) {
        gather_o(sb, cta, warp, lane, tag32);
        PROF(7);
    }
    if (WD_TAIL && ffn) down_proj();
    PROF(6);
    {
        uint32_t wa[8][2][4];
        auto load_wo = [&]() {
            mbar_wait(bar_full + 8 * st, ph, 7);
            const uint32_t base = sb + st * STAGE_BYTES + (warp >> 1) * 16384 + offA;
#pragma unroll
            for (int ks = 0; ks < 8; ks++) {
                ldsm4t(wa[ks][0], base + ks * 2048 + swz0);
                ldsm4t(wa[ks][1], base + ks * 2048 + swz1);
            }
        };
        if (GW) load_wo();
        const int b0 = 2 * (c & 1);
        const float g0 = lds_f32(sb + OFF_GS + b0 * 4), g1 = lds_f32(sb + OFF_GS + b0 * 4 + 4);
        const float f0 = lds_f32(sb + OFF_GS + 16 + b0 * 4), f1 = lds_f32(sb + OFF_GS + 16 + b0 * 4 + 4);
        const bool hi = c >= 2;
        float bv[2][2];
#pragma unroll
        for (int i = 0; i < 2; i++) { bv[i][0] = f0 * (hi ? yb[i][2] : yb[i][0]); bv[i][1] = f1 * (hi ? yb[i][3] : yb[i][1]); }
        uint32_t* dst = g_y + ((b0 * 32 + nn * 8 + warp * 2) * 32 + kk) * 16 + r + 8 * (c >> 1);
        bar_sync(GW ? 4 : 1, GW ? 256 : 128);
        uint32_t ob[4][4];
#pragma unroll
        for (int k2 = 0; k2 < 4; k2++) ldsm4(ob[k2], sb + OFF_OS + (lane & 3) * QS_STRIDE + (lane >> 3) * 16 + k2 * 64);
        if (!GW) load_wo();
        float ya[2][4][4];
#pragma unroll
        for (int i = 0; i < 2; i++)
#pragma unroll
            for (int j = 0; j < 4; j++) { ya[i][j][0] = ya[i][j][1] = ya[i][j][2] = ya[i][j][3] = 0.f; }
#pragma unroll
        for (int ks = 0; ks < 8; ks++) {
            mma16816(ya[0][ks & 3], wa[ks][0], ob[ks >> 1][2 * (ks & 1)], ob[ks >> 1][2 * (ks & 1) + 1]);
            mma16816(ya[1][ks & 3], wa[ks][1], ob[ks >> 1][2 * (ks & 1)], ob[ks >> 1][2 * (ks & 1) + 1]);
        }
#pragma unroll
        for (int i = 0; i < 2; i++) {
            const float av0 = hi ? (ya[i][0][2] + ya[i][1][2]) + (ya[i][2][2] + ya[i][3][2]) : (ya[i][0][0] + ya[i][1][0]) + (ya[i][2][0] + ya[i][3][0]);
            const float av1 = hi ? (ya[i][0][3] + ya[i][1][3]) + (ya[i][2][3] + ya[i][3][3]) : (ya[i][0][1] + ya[i][1][1]) + (ya[i][2][1] + ya[i][3][1]);
            const float y0 = fmaf(g0, av0, bv[i][0]), y1 = fmaf(g1, av1, bv[i][1]);
            stg_rlx(dst + i * 32 * 16, (__float_as_uint(y0) & ~1u) | tag1);
            stg_rlx(dst + i * 32 * 16 + 32 * 32 * 16, (__float_as_uint(y1) & ~1u) | tag1);
        }
    }
    PROF(8);
    if (!FINAL_PROD && warp == 0) final_reduce(out, cta, lane, tag32);
}

typedef CUresult (*EncodeFn)(CUtensorMap*, CUtensorMapDataType, cuuint32_t, void*, const cuuint64_t*, const cuuint64_t*,
                             const cuuint32_t*, const cuuint32_t*, CUtensorMapInterleave, CUtensorMapSwizzle,
                             CUtensorMapL2promotion, CUtensorMapFloatOOBfill);

void make_map(EncodeFn enc, CUtensorMap* m, const void* p, int rank, cuuint64_t d0, cuuint64_t d1, cuuint64_t d2,
              cuuint64_t s1, cuuint64_t s2, cuuint32_t b0, cuuint32_t b1, cuuint32_t b2, CUtensorMapSwizzle sw) {
    cuuint64_t dims[3] = {d0, d1, d2}, strides[2] = {s1, s2};
    cuuint32_t box[3] = {b0, b1, b2}, es[3] = {1, 1, 1};
    enc(m, CU_TENSOR_MAP_DATA_TYPE_BFLOAT16, rank, const_cast<void*>(p), dims, strides, box, es,
        CU_TENSOR_MAP_INTERLEAVE_NONE, sw, CU_TENSOR_MAP_L2_PROMOTION_L2_256B, CU_TENSOR_MAP_FLOAT_OOB_FILL_NONE);
}

}

extern "C" void kernel_launch(void* const* d_in, const int* in_sizes, int n_in, void* d_out, int out_size) {
    (void)in_sizes; (void)n_in; (void)out_size;
    static EncodeFn enc = nullptr;
    if (!enc) {
        void* fn = nullptr;
        cudaDriverEntryPointQueryResult qr;
        cudaGetDriverEntryPoint("cuTensorMapEncodeTiled", &fn, cudaEnableDefault, &qr);
        enc = (EncodeFn)fn;
        cudaFuncSetAttribute(fused_decode_kernel, cudaFuncAttributeMaxDynamicSharedMemorySize, SMEM_BYTES);
    }
    CUtensorMap mK, mV, mWq, mWg, mWu, mWd, mWo;
    make_map(enc, &mK, d_in[1], 3, 64, 4 * 8 * 16384, 2, 256, 128, 64, TILE, 2, CU_TENSOR_MAP_SWIZZLE_128B);
    make_map(enc, &mV, d_in[2], 3, 64, 4 * 8 * 16384, 2, 256, 128, 64, TILE, 2, CU_TENSOR_MAP_SWIZZLE_128B);
    make_map(enc, &mWq, d_in[3], 2, 4096, 512, 1, 8192, 0, 32, 256, 1, CU_TENSOR_MAP_SWIZZLE_64B);
    make_map(enc, &mWg, d_in[6], 2, 1792, 512, 1, 3584, 0, 16, 256, 1, CU_TENSOR_MAP_SWIZZLE_32B);
    make_map(enc, &mWu, d_in[7], 2, 1792, 512, 1, 3584, 0, 16, 256, 1, CU_TENSOR_MAP_SWIZZLE_32B);
    make_map(enc, &mWd, d_in[8], 3, 64, 1792, 8, 1024, 128, 64, 64, 2, CU_TENSOR_MAP_SWIZZLE_128B);
    make_map(enc, &mWo, d_in[4], 3, 64, 4096, 8, 1024, 128, 64, 128, 2, CU_TENSOR_MAP_SWIZZLE_128B);
    fused_decode_kernel<<<NCTA, NTHREADS, SMEM_BYTES>>>(mK, mV, mWq, mWg, mWu, mWd, mWo,
        (const __nv_bfloat16*)d_in[0], (const __nv_bfloat16*)d_in[9], (__nv_bfloat16*)d_out,
        (const uint8_t*)d_in[3], (const uint8_t*)d_in[1], (const uint8_t*)d_in[2], (const uint8_t*)d_in[6], (const uint8_t*)d_in[7]);
}
```

```cpp
#include <cuda_runtime.h>
#include <cuda_bf16.h>
#include <cuda.h>
#include <stdint.h>

namespace {

constexpr int NCTA        = 128;
constexpr int NTHREADS    = 448;
constexpr int STAGE_BYTES = 32768;
constexpr int NSTAGES     = 6;
constexpr int TILE        = 128;
constexpr int NTILES      = 4096 / TILE;
constexpr int NFFN        = 112;
constexpr int TILE_WG     = 1;
constexpr int TILE_H      = 6;
constexpr int IT_WG       = 2 * TILE_WG + 1;
constexpr int IT_WD       = 2 * NTILES + 2;

constexpr int INIT_ITEMS  = 2;
constexpr int WINDOW      = 2;
constexpr int WSTART      = 4;
constexpr int WCAP        = 5;
constexpr int CX          = 352;
constexpr int CXL         = 256;
constexpr int GO_GATHER   = 4;
constexpr int GO_REDUCE   = 2;

constexpr int OFF_BAR = NSTAGES * STAGE_BYTES;
constexpr int OFF_XS  = OFF_BAR + 256;
constexpr int XS_STRIDE = 1040;
constexpr int OFF_QS  = OFF_XS + 4 * XS_STRIDE;
constexpr int QS_STRIDE = 272;
constexpr int OFF_OS  = OFF_QS + 4 * QS_STRIDE;
constexpr int OFF_HS  = OFF_OS + 4 * QS_STRIDE;
constexpr int HS_STRIDE = 144;
constexpr int OFF_SO  = OFF_HS + 4 * HS_STRIDE;
constexpr int SO_STRIDE = 136;
constexpr int OFF_SM  = OFF_SO + 16 * SO_STRIDE * 4;
constexpr int OFF_GS  = OFF_SM + 128;
constexpr int OFF_UP  = OFF_GS + 32;
constexpr int OFF_FR  = OFF_UP + 256;
constexpr int SMEM_USED  = OFF_FR + 512;
constexpr int SMEM_BYTES = SMEM_USED + 1024;

__device__ uint32_t g_epoch[NCTA];
__device__ __align__(128) uint32_t g_q[4 * 4096];
__device__ __align__(128) uint32_t g_h[4 * 1792];
__device__ __align__(128) uint32_t g_part[4 * 32 * 4 * 128];
__device__ __align__(128) uint32_t g_y[4 * 16 * 32 * 32];
__device__ __align__(128) uint32_t g_cnt;

constexpr int SPIN_LIMIT = 1 << 22;

__device__ __forceinline__ uint32_t smem_u32(const void* p) { return (uint32_t)__cvta_generic_to_shared(p); }
__device__ __forceinline__ void mbar_init(uint32_t bar, uint32_t cnt) {
    asm volatile("mbarrier.init.shared::cta.b64 [%0], %1;" :: "r"(bar), "r"(cnt) : "memory");
}
__device__ __forceinline__ void mbar_expect_tx(uint32_t bar, uint32_t bytes) {
    asm volatile("mbarrier.arrive.expect_tx.shared::cta.b64 _, [%0], %1;" :: "r"(bar), "r"(bytes) : "memory");
}
__device__ __forceinline__ void mbar_arrive(uint32_t bar) {
    asm volatile("mbarrier.arrive.shared::cta.b64 _, [%0];" :: "r"(bar) : "memory");
}
__device__ __forceinline__ bool mbar_try_wait(uint32_t bar, uint32_t parity) {
    uint32_t ok;
    asm volatile("{\n.reg .pred p;\nmbarrier.try_wait.parity.shared::cta.b64 p, [%1], %2;\nselp.u32 %0, 1, 0, p;\n}"
                 : "=r"(ok) : "r"(bar), "r"(parity) : "memory");
    return ok;
}
__device__ __forceinline__ void mbar_wait(uint32_t bar, uint32_t parity) {
    int it = 0;
    while (!mbar_try_wait(bar, parity)) { if (++it > SPIN_LIMIT) __trap(); }
}
__device__ __forceinline__ void bulk_load(uint32_t dst, const void* src, uint32_t bytes, uint32_t bar) {
    asm volatile("cp.async.bulk.shared::cluster.global.mbarrier::complete_tx::bytes [%0], [%1], %2, [%3];"
                 :: "r"(dst), "l"(src), "r"(bytes), "r"(bar) : "memory");
}
__device__ __forceinline__ void tma2d(uint32_t dst, const CUtensorMap* tm, int c0, int c1, uint32_t bar) {
    asm volatile("cp.async.bulk.tensor.2d.shared::cluster.global.mbarrier::complete_tx::bytes [%0], [%1, {%3, %4}], [%2];"
                 :: "r"(dst), "l"(tm), "r"(bar), "r"(c0), "r"(c1) : "memory");
}
__device__ __forceinline__ void tma3d(uint32_t dst, const CUtensorMap* tm, int c0, int c1, int c2, uint32_t bar) {
    asm volatile("cp.async.bulk.tensor.3d.shared::cluster.global.mbarrier::complete_tx::bytes [%0], [%1, {%3, %4, %5}], [%2];"
                 :: "r"(dst), "l"(tm), "r"(bar), "r"(c0), "r"(c1), "r"(c2) : "memory");
}
__device__ __forceinline__ void tma3d_h(uint32_t dst, const CUtensorMap* tm, int c0, int c1, int c2, uint32_t bar, uint64_t pol) {
    asm volatile("cp.async.bulk.tensor.3d.shared::cluster.global.mbarrier::complete_tx::bytes.L2::cache_hint [%0], [%1, {%3, %4, %5}], [%2], %6;"
                 :: "r"(dst), "l"(tm), "r"(bar), "r"(c0), "r"(c1), "r"(c2), "l"(pol) : "memory");
}
__device__ __forceinline__ void prefetch_map(const CUtensorMap* tm) {
    asm volatile("prefetch.tensormap [%0];" :: "l"(tm) : "memory");
}
__device__ __forceinline__ void ldsm4(uint32_t (&r)[4], uint32_t addr) {
    asm volatile("ldmatrix.sync.aligned.m8n8.x4.shared.b16 {%0,%1,%2,%3}, [%4];"
                 : "=r"(r[0]), "=r"(r[1]), "=r"(r[2]), "=r"(r[3]) : "r"(addr) : "memory");
}
__device__ __forceinline__ void ldsm4t(uint32_t (&r)[4], uint32_t addr) {
    asm volatile("ldmatrix.sync.aligned.m8n8.x4.trans.shared.b16 {%0,%1,%2,%3}, [%4];"
                 : "=r"(r[0]), "=r"(r[1]), "=r"(r[2]), "=r"(r[3]) : "r"(addr) : "memory");
}
__device__ __forceinline__ void mma16816(float (&d)[4], const uint32_t (&a)[4], uint32_t b0, uint32_t b1) {
    asm volatile("mma.sync.aligned.m16n8k16.row.col.f32.bf16.bf16.f32 {%0,%1,%2,%3}, {%4,%5,%6,%7}, {%8,%9}, {%0,%1,%2,%3};"
                 : "+f"(d[0]), "+f"(d[1]), "+f"(d[2]), "+f"(d[3])
                 : "r"(a[0]), "r"(a[1]), "r"(a[2]), "r"(a[3]), "r"(b0), "r"(b1));
}
__device__ __forceinline__ uint32_t movm_t(uint32_t a) {
    uint32_t d;
    asm volatile("movmatrix.sync.aligned.m8n8.trans.b16 %0, %1;" : "=r"(d) : "r"(a));
    return d;
}
__device__ __forceinline__ uint32_t pack_bf16(float lo, float hi) {
    uint32_t d;
    asm("cvt.rn.bf16x2.f32 %0, %1, %2;" : "=r"(d) : "f"(hi), "f"(lo));
    return d;
}
__device__ __forceinline__ float ex2(float x) {
    float y;
    asm("ex2.approx.ftz.f32 %0, %1;" : "=f"(y) : "f"(x));
    return y;
}
__device__ __forceinline__ float bf16r(float x) { return __bfloat162float(__float2bfloat16_rn(x)); }
__device__ __forceinline__ uint32_t bf16bits(float x) { return (uint32_t)__bfloat16_as_ushort(__float2bfloat16_rn(x)); }
__device__ __forceinline__ void bar_sync(int id, int n) { asm volatile("bar.sync %0, %1;" :: "r"(id), "r"(n) : "memory"); }
__device__ __forceinline__ void bar_arrive(int id, int n) { asm volatile("bar.arrive %0, %1;" :: "r"(id), "r"(n) : "memory"); }

__device__ __forceinline__ uint4 ldg_rlx4(const uint32_t* p) {
    uint4 v;
    asm volatile("ld.relaxed.gpu.global.v4.u32 {%0,%1,%2,%3}, [%4];" : "=r"(v.x), "=r"(v.y), "=r"(v.z), "=r"(v.w) : "l"(p) : "memory");
    return v;
}
__device__ __forceinline__ uint32_t ldg_rlx(const uint32_t* p) {
    uint32_t v;
    asm volatile("ld.relaxed.gpu.global.u32 %0, [%1];" : "=r"(v) : "l"(p) : "memory");
    return v;
}
__device__ __forceinline__ void ldg_rlx4_if(uint4& v, const uint32_t* p, uint32_t pred) {
    asm volatile("{\n.reg .pred p;\nsetp.ne.u32 p, %5, 0;\n@p ld.relaxed.gpu.global.v4.u32 {%0,%1,%2,%3}, [%4];\n}"
                 : "+r"(v.x), "+r"(v.y), "+r"(v.z), "+r"(v.w) : "l"(p), "r"(pred) : "memory");
}
__device__ __forceinline__ void red_add(uint32_t* p, uint32_t v) {
    asm volatile("red.relaxed.gpu.global.add.u32 [%0], %1;" :: "l"(p), "r"(v) : "memory");
}
__device__ __forceinline__ void stg_rlx(uint32_t* p, uint32_t v) {
    asm volatile("st.relaxed.gpu.global.u32 [%0], %1;" :: "l"(p), "r"(v) : "memory");
}
__device__ __forceinline__ void stg_rlx4(uint32_t* p, uint32_t a, uint32_t b, uint32_t c, uint32_t d) {
    asm volatile("st.relaxed.gpu.global.v4.u32 [%0], {%1,%2,%3,%4};" :: "l"(p), "r"(a), "r"(b), "r"(c), "r"(d) : "memory");
}
__device__ __forceinline__ float lds_f32(uint32_t a) { float v; asm volatile("ld.shared.f32 %0, [%1];" : "=f"(v) : "r"(a) : "memory"); return v; }
__device__ __forceinline__ float4 lds_f32x4(uint32_t a) {
    float4 v; asm volatile("ld.shared.v4.f32 {%0,%1,%2,%3}, [%4];" : "=f"(v.x), "=f"(v.y), "=f"(v.z), "=f"(v.w) : "r"(a) : "memory"); return v;
}
__device__ __forceinline__ uint4 lds_u32x4(uint32_t a) {
    uint4 v; asm volatile("ld.shared.v4.u32 {%0,%1,%2,%3}, [%4];" : "=r"(v.x), "=r"(v.y), "=r"(v.z), "=r"(v.w) : "r"(a) : "memory"); return v;
}
__device__ __forceinline__ void sts_f32(uint32_t a, float v) { asm volatile("st.shared.f32 [%0], %1;" :: "r"(a), "f"(v) : "memory"); }
__device__ __forceinline__ void sts_u32x2(uint32_t a, uint32_t x, uint32_t y) { asm volatile("st.shared.v2.u32 [%0], {%1,%2};" :: "r"(a), "r"(x), "r"(y) : "memory"); }

template <int KSTRIDE>
__device__ __forceinline__ void proj512(float (&out)[4], uint32_t a_addr, uint32_t x_addr) {
    float acc[4][4];
#pragma unroll
    for (int i = 0; i < 4; i++) { acc[i][0] = acc[i][1] = acc[i][2] = acc[i][3] = 0.f; }
#pragma unroll 4
    for (int k2 = 0; k2 < 16; k2++) {
        uint32_t b[4], a0[4], a1[4];
        ldsm4(b, x_addr + k2 * 64);
        ldsm4t(a0, a_addr + (2 * k2) * KSTRIDE);
        ldsm4t(a1, a_addr + (2 * k2 + 1) * KSTRIDE);
        mma16816(acc[(2 * k2) & 3], a0, b[0], b[1]);
        mma16816(acc[(2 * k2 + 1) & 3], a1, b[2], b[3]);
    }
#pragma unroll
    for (int i = 0; i < 4; i++) out[i] = (acc[0][i] + acc[1][i]) + (acc[2][i] + acc[3][i]);
}

__device__ __forceinline__ void gather_o(uint32_t sb, int cta, int batch, int lane, uint32_t tag32) {
    const uint32_t tag1 = tag32 & 1u;
    const uint32_t* src = g_part + (batch * 32 + (cta >> 2)) * 4 * 128 + lane * 4;
    uint4 ov[4];
    uint32_t need = 0xFu;
#pragma unroll
    for (int s = 0; s < 4; s++) ov[s] = make_uint4(0, 0, 0, 0);
    int it = 0;
    while (true) {
#pragma unroll
        for (int s = 0; s < 4; s++) ldg_rlx4_if(ov[s], src + s * 128, need & (1u << s));
#pragma unroll
        for (int s = 0; s < 4; s++)
            if (__all_sync(0xffffffffu, (((ov[s].x ^ tag1) | (ov[s].y ^ tag1) | (ov[s].z ^ tag1) | (ov[s].w ^ tag1)) & 1u) == 0)) need &= ~(1u << s);
        if (need == 0) break;
        if (++it > SPIN_LIMIT) __trap();
    }
    float Ms[4], Ls[4], M = -INFINITY;
#pragma unroll
    for (int s = 0; s < 4; s++) {
        Ms[s] = __uint_as_float(__ballot_sync(0xffffffffu, ov[s].x & 2u));
        Ls[s] = __uint_as_float(__ballot_sync(0xffffffffu, ov[s].y & 2u));
        M = fmaxf(M, Ms[s]);
    }
    float L = 0.f, a0 = 0.f, a1 = 0.f, a2 = 0.f, a3 = 0.f;
#pragma unroll
    for (int s = 0; s < 4; s++) {
        const float w = ex2(Ms[s] - M);
        L  = fmaf(w, Ls[s], L);
        a0 = fmaf(w, __uint_as_float(ov[s].x & ~3u), a0); a1 = fmaf(w, __uint_as_float(ov[s].y & ~3u), a1);
        a2 = fmaf(w, __uint_as_float(ov[s].z), a2);       a3 = fmaf(w, __uint_as_float(ov[s].w), a3);
    }
    const float inv = 1.f / L;
    sts_u32x2(sb + OFF_OS + batch * QS_STRIDE + lane * 8, pack_bf16(a0 * inv, a1 * inv), pack_bf16(a2 * inv, a3 * inv));
}

__device__ __forceinline__ void final_reduce(__nv_bfloat16* __restrict__ out, uint32_t sb, int rd, int w, int lane, uint32_t tag32) {
    const uint32_t tag1 = tag32 & 1u;
    const uint32_t* src = g_y + (rd * 32 + w * 8) * 32 + lane * 4;
    uint4 v0, v1; int it = 0;
    while (true) {
        v0 = ldg_rlx4(src); v1 = ldg_rlx4(src + 128);
        const uint32_t bad = (v0.x ^ tag1) | (v0.y ^ tag1) | (v0.z ^ tag1) | (v0.w ^ tag1) | (v1.x ^ tag1) | (v1.y ^ tag1) | (v1.z ^ tag1) | (v1.w ^ tag1);
        if (__all_sync(0xffffffffu, (bad & 1u) == 0)) break;
        if (++it > SPIN_LIMIT) __trap();
    }
    float s0 = __uint_as_float(v0.x) + __uint_as_float(v1.x), s1 = __uint_as_float(v0.y) + __uint_as_float(v1.y);
    float s2 = __uint_as_float(v0.z) + __uint_as_float(v1.z), s3 = __uint_as_float(v0.w) + __uint_as_float(v1.w);
#pragma unroll
    for (int o = 8; o < 32; o <<= 1) {
        s0 += __shfl_xor_sync(0xffffffffu, s0, o); s1 += __shfl_xor_sync(0xffffffffu, s1, o);
        s2 += __shfl_xor_sync(0xffffffffu, s2, o); s3 += __shfl_xor_sync(0xffffffffu, s3, o);
    }
    if (lane < 8) asm volatile("st.shared.v4.f32 [%0], {%1,%2,%3,%4};" :: "r"(sb + OFF_FR + w * 128 + lane * 16), "f"(s0), "f"(s1), "f"(s2), "f"(s3) : "memory");
    if (w != 0) { bar_arrive(5, 128); return; }
    bar_sync(5, 128);
    const uint32_t a = sb + OFF_FR + (4 * (lane & 7) + (lane >> 3)) * 4;
    const float y = (lds_f32(a) + lds_f32(a + 128)) + (lds_f32(a + 256) + lds_f32(a + 384));
    out[rd * 32 + lane] = __float2bfloat16_rn(y);
}

__global__ void __launch_bounds__(NTHREADS, 1)
fused_decode_kernel(const __grid_constant__ CUtensorMap mapK, const __grid_constant__ CUtensorMap mapV,
                    const __grid_constant__ CUtensorMap mapWq, const __grid_constant__ CUtensorMap mapWg,
                    const __grid_constant__ CUtensorMap mapWu, const __grid_constant__ CUtensorMap mapWd,
                    const __grid_constant__ CUtensorMap mapWo,
                    const __nv_bfloat16* __restrict__ x, const __nv_bfloat16* __restrict__ gate_w,
                    __nv_bfloat16* __restrict__ out, const uint8_t* __restrict__ wq_raw)
{
    if (threadIdx.x < 128) {
        asm volatile("prefetch.global.L2 [%0];" :: "l"(wq_raw + (size_t)blockIdx.x * STAGE_BYTES + threadIdx.x * 256u));
    }
    extern __shared__ uint8_t smem_raw[];
    const uint32_t sb = (smem_u32(smem_raw) + 1023u) & ~1023u;
    const int cta = blockIdx.x, tid = threadIdx.x, warp = tid >> 5, lane = tid & 31;
    const bool ffn = cta < NFFN;
    const uint32_t bar_full = sb + OFF_BAR, bar_empty = sb + OFF_BAR + 8 * NSTAGES, bar_go = sb + OFF_BAR + 16 * NSTAGES;

    if (warp == 4) {
        const int nitems = (ffn ? 4 : 2) + 2 * NTILES;
        uint64_t pol;
        asm volatile("createpolicy.fractional.L2::evict_first.b64 %0, 1.0;" : "=l"(pol));
        auto issue = [&](int it, int st) {
            const uint32_t dst = sb + st * STAGE_BYTES, bar = bar_full + 8 * st;
            if (it == 0) {
                mbar_expect_tx(bar, STAGE_BYTES + 4096);
                tma2d(dst, &mapWq, cta * 32, 0, bar);
                tma2d(dst + 16384, &mapWq, cta * 32, 256, bar);
#pragma unroll
                for (int b = 0; b < 4; b++) bulk_load(sb + OFF_XS + b * XS_STRIDE, x + b * 512, 1024, bar);
            } else if (ffn && it == IT_WG) {
                mbar_expect_tx(bar, STAGE_BYTES);
                tma2d(dst,         &mapWg, cta * 16, 0,   bar);
                tma2d(dst + 8192,  &mapWg, cta * 16, 256, bar);
                tma2d(dst + 16384, &mapWu, cta * 16, 0,   bar);
                tma2d(dst + 24576, &mapWu, cta * 16, 256, bar);
            } else if (ffn && it == IT_WD) {
                mbar_expect_tx(bar, 16384);
                tma3d(dst, &mapWd, 0, (cta >> 2) * 64, (cta & 3) * 2, bar);
            } else if (it == nitems - 1) {
                mbar_expect_tx(bar, STAGE_BYTES);
                tma3d(dst, &mapWo, 0, (cta >> 2) * 128, (cta & 3) * 2, bar);
            } else {
                const int j = it - 1 - (ffn ? (it > IT_WG) + (it > IT_WD) : 0);
                mbar_expect_tx(bar, STAGE_BYTES);
                const int row = cta * 4096 + (j >> 1) * TILE;
                tma3d_h(dst, (j & 1) ? &mapV : &mapK, 0, row, 0, bar, pol);
            }
        };
        if (lane == 0) {
#pragma unroll
            for (int i = 0; i < NSTAGES; i++) { mbar_init(bar_full + 8 * i, 1); mbar_init(bar_empty + 8 * i, 5); }
            mbar_init(bar_go, 1);
            mbar_init(bar_go + 8, 1);
            asm volatile("fence.mbarrier_init.release.cluster;" ::: "memory");
            asm volatile("fence.proxy.async.shared::cta;" ::: "memory");
#pragma unroll
            for (int i = 0; i < INIT_ITEMS; i++) issue(i, i);
        }
        __syncwarp();
        __syncthreads();
        const uint32_t tag32 = *(volatile const uint32_t*)&g_epoch[cta] + 1u;
        const int first_late = nitems - (ffn ? 2 : 1);
        int st = INIT_ITEMS % NSTAGES, ph = 1;
        int fst = (INIT_ITEMS - WINDOW) % NSTAGES, fph = 0;
        int nl = INIT_ITEMS - WINDOW;
        auto is_kv = [&](int it) { return it > 0 && it < first_late && !(ffn && it == IT_WG); };
        if (lane == 0) {
            const uint32_t cnt0 = (tag32 - 1u) * (uint32_t)(NCTA * 2 * NTILES);
            uint32_t cnt = cnt0;
            for (int it = INIT_ITEMS; it < nitems; it++) {
                const int win = it < WSTART ? WINDOW : WCAP;
                while (nl <= it - win) {
                    mbar_wait(bar_full + 8 * fst, fph);
                    if (++fst == NSTAGES) { fst = 0; fph ^= 1; }
                    nl++;
                }
                const bool late = it >= first_late;
                if (late || is_kv(it)) {
                    const int j = late ? 2 * NTILES : it - 1 - (ffn ? (it > IT_WG) + (it > IT_WD) : 0);
                    const int thr = NCTA * j + (cta & (NCTA - 1)) - (late ? CXL : CX);
                    int spin = 0;
                    while ((int)(cnt - cnt0) < thr) {
                        cnt = ldg_rlx(&g_cnt);
                        if (++spin > SPIN_LIMIT) __trap();
                    }
                }
                if (it >= NSTAGES) mbar_wait(bar_empty + 8 * st, ph);
                issue(it, st);
                if (++st == NSTAGES) { st = 0; ph ^= 1; }
                cnt = ldg_rlx(&g_cnt);
            }
        }
        __syncwarp();
        if (lane == 0) g_epoch[cta] = tag32;
        return;
    }

    if (warp == 9) {
        __syncthreads();
        if (lane == 0) {
            const int nkv = 2 * NTILES + (ffn ? 2 : 1);
            int st = 0, ph = 0;
            for (int it = 0; it < nkv; it++) {
                mbar_wait(bar_full + 8 * st, ph);
                if (it > 0 && !(ffn && it == IT_WG)) red_add(&g_cnt, 1u);
                if (it == nkv - GO_GATHER) mbar_arrive(bar_go);
                if (it == nkv - GO_REDUCE) mbar_arrive(bar_go + 8);
                mbar_arrive(bar_empty + 8 * st);
                if (++st == NSTAGES) { st = 0; ph ^= 1; }
            }
        }
        return;
    }
    if (warp > 9) {
        const uint32_t t32 = *(volatile const uint32_t*)&g_epoch[cta] + 1u;
        __syncthreads();
        if ((cta & 1) == 0) {
            mbar_wait(bar_go + 8, 0);
            final_reduce(out, sb, cta >> 1, warp - 10, lane, t32);
        }
        return;
    }
    if (warp > 4) {
        const uint32_t t32 = *(volatile const uint32_t*)&g_epoch[cta] + 1u;
        __syncthreads();
        mbar_wait(bar_go, 0);
        gather_o(sb, cta, warp - 5, lane, t32);
        bar_arrive(4, 256);
        return;
    }

    if (warp == 0 && lane < 7) {
        const CUtensorMap* pm = lane == 0 ? &mapWq : lane == 1 ? &mapK : lane == 2 ? &mapV : lane == 3 ? &mapWg : lane == 4 ? &mapWu : lane == 5 ? &mapWd : &mapWo;
        prefetch_map(pm);
    }
    const uint32_t epoch = *(volatile const uint32_t*)&g_epoch[cta];
    const uint4 gw0 = __ldg(reinterpret_cast<const uint4*>(gate_w) + lane * 2);
    const uint4 gw1 = __ldg(reinterpret_cast<const uint4*>(gate_w) + lane * 2 + 1);
    __syncthreads();
    const uint32_t tag32 = epoch + 1u, tag16 = (tag32 & 0x7fffu) | 0x8000u, tag1 = tag32 & 1u;

    const int r = lane >> 2, c = lane & 3;
    const int bq = cta >> 5, hkv = (cta >> 2) & 7, sq = cta & 3;
    const int kk = cta >> 2, nn = cta & 3;
    int st = 0, ph = 0;
    auto advance = [&]() { if (++st == NSTAGES) { st = 0; ph ^= 1; } };
    auto release = [&]() { __syncwarp(); if (lane == 0) mbar_arrive(bar_empty + 8 * st); };

    const uint32_t xs_lane = sb + OFF_XS + (lane & 3) * XS_STRIDE + (lane >> 3) * 16;

    mbar_wait(bar_full, 0);
    if (warp < 2) {
        float d[4];
        const int k = (lane & 7) + 8 * (lane >> 4);
        const int cc = 2 * warp + ((lane >> 3) & 1);
        proj512<1024>(d, sb + k * 64 + ((cc ^ ((lane & 7) >> 1)) << 4), xs_lane);
        const float v0 = (c >= 2) ? d[2] : d[0], v1 = (c >= 2) ? d[3] : d[1];
        uint32_t* dst = g_q + (2 * (c & 1)) * 4096 + cta * 32 + warp * 16 + r + 8 * (c >> 1);
        stg_rlx(dst, (bf16bits(v0) << 16) | tag16);
        stg_rlx(dst + 4096, (bf16bits(v1) << 16) | tag16);
    }
    release(); advance();
    {
        const uint4 x0 = lds_u32x4(sb + OFF_XS + warp * XS_STRIDE + lane * 32);
        const uint4 x1 = lds_u32x4(sb + OFF_XS + warp * XS_STRIDE + lane * 32 + 16);
        const uint32_t xv[8] = {x0.x, x0.y, x0.z, x0.w, x1.x, x1.y, x1.z, x1.w};
        const uint32_t wv[8] = {gw0.x, gw0.y, gw0.z, gw0.w, gw1.x, gw1.y, gw1.z, gw1.w};
        float z = 0.f;
#pragma unroll
        for (int i = 0; i < 8; i++) {
            const __nv_bfloat162 p = __hmul2(*reinterpret_cast<const __nv_bfloat162*>(&xv[i]), *reinterpret_cast<const __nv_bfloat162*>(&wv[i]));
            z += __low2float(p) + __high2float(p);
        }
#pragma unroll
        for (int o = 16; o > 0; o >>= 1) z += __shfl_xor_sync(0xffffffffu, z, o);
        z = bf16r(z);
        const float g = bf16r(1.f / (1.f + expf(-z)));
        if (lane == 0) { sts_f32(sb + OFF_GS + warp * 4, g); sts_f32(sb + OFF_GS + 16 + warp * 4, bf16r(1.f - g)); }
    }
    {
        const uint32_t* src = g_q + bq * 4096 + (hkv * 4 + warp) * 128 + lane * 4;
        uint4 v; int it = 0;
        mbar_wait(bar_full + 8 * 2, 0);
        while (true) {
            v = ldg_rlx4(src);
            const bool ok = ((v.x & 0xffffu) == tag16) && ((v.y & 0xffffu) == tag16) && ((v.z & 0xffffu) == tag16) && ((v.w & 0xffffu) == tag16);
            if (__all_sync(0xffffffffu, ok)) break;
            if (++it > SPIN_LIMIT) __trap();
        }
        sts_u32x2(sb + OFF_QS + warp * QS_STRIDE + lane * 8, __byte_perm(v.x, v.y, 0x7632), __byte_perm(v.z, v.w, 0x7632));
    }
    bar_sync(1, 128);
    uint32_t qf[8][2];
#pragma unroll
    for (int k2 = 0; k2 < 4; k2++) {
        uint32_t b[4];
        ldsm4(b, sb + OFF_QS + (lane & 3) * QS_STRIDE + (lane >> 3) * 16 + k2 * 64);
        qf[2 * k2][0] = b[0]; qf[2 * k2][1] = b[1]; qf[2 * k2 + 1][0] = b[2]; qf[2 * k2 + 1][1] = b[3];
    }

    const float sl2 = 0.08838834764831845f * 1.4426950408889634f;
    float O[8][4];
#pragma unroll
    for (int t = 0; t < 8; t++) { O[t][0] = O[t][1] = O[t][2] = O[t][3] = 0.f; }
    float m0 = -INFINITY, m1 = -INFINITY, l0 = 0.f, l1 = 0.f;
    const uint32_t offK = (32 * warp + (lane & 7) + 8 * ((lane >> 3) & 1)) * 128 + (((lane >> 4) ^ (lane & 7)) << 4);
    const uint32_t offV = (32 * warp + (lane & 7) + 8 * (lane >> 4)) * 128 + ((((lane >> 3) & 1) ^ (lane & 7)) << 4);

    const int brow = (lane & 7) >> 1;
    float yb[2][4];
#pragma unroll
    for (int i = 0; i < 2; i++) { yb[i][0] = yb[i][1] = yb[i][2] = yb[i][3] = 0.f; }
    const uint32_t offA = ((lane & 7) + 8 * (lane >> 4)) * 128;
    const uint32_t swz0 = ((2 * ((2 * warp) & 3) + ((lane >> 3) & 1)) ^ (lane & 7)) << 4;
    const uint32_t swz1 = ((2 * ((2 * warp + 1) & 3) + ((lane >> 3) & 1)) ^ (lane & 7)) << 4;
    const int pslot = (bq * 32 + hkv * 4 + warp) * 4 + sq;

#pragma unroll 1
    for (int tile = 0; tile < NTILES; tile++) {
        if (ffn && tile == TILE_WG) {
            if (warp >= 2) {
                mbar_wait(bar_full + 8 * st, ph);
                float d[4];
                const int k = (lane & 7) + 8 * (lane >> 4);
                const int cc = (lane >> 3) & 1;
                proj512<512>(d, sb + st * STAGE_BYTES + (warp - 2) * 16384 + k * 32 + ((cc ^ ((lane & 7) >> 2)) << 4), xs_lane);
                const float v0 = bf16r((c >= 2) ? d[2] : d[0]), v1 = bf16r((c >= 2) ? d[3] : d[1]);
                release();
                if (warp == 3) { sts_f32(sb + OFF_UP + lane * 8, v0); sts_f32(sb + OFF_UP + lane * 8 + 4, v1); }
                bar_sync(2, 64);
                if (warp == 2) {
                    const float u0 = lds_f32(sb + OFF_UP + lane * 8), u1 = lds_f32(sb + OFF_UP + lane * 8 + 4);
                    const float h0 = (v0 > 0.f ? v0 : 0.f * v0) * u0, h1 = (v1 > 0.f ? v1 : 0.f * v1) * u1;
                    uint32_t* dst = g_h + (2 * (c & 1)) * 1792 + cta * 16 + r + 8 * (c >> 1);
                    stg_rlx(dst, (bf16bits(h0) << 16) | tag16);
                    stg_rlx(dst + 1792, (bf16bits(h1) << 16) | tag16);
                }
            } else {
                release();
            }
            advance();
        }
        if (ffn && tile == TILE_H) {
            if (warp < 2) {
                const int b = tid >> 4, f4 = (tid & 15) * 4;
                const uint32_t* src = g_h + b * 1792 + kk * 64 + f4;
                uint4 v; int it = 0;
                while (true) {
                    v = ldg_rlx4(src);
                    const bool ok = ((v.x & 0xffffu) == tag16) && ((v.y & 0xffffu) == tag16) && ((v.z & 0xffffu) == tag16) && ((v.w & 0xffffu) == tag16);
                    if (__all_sync(0xffffffffu, ok)) break;
                    if (++it > SPIN_LIMIT) __trap();
                }
                sts_u32x2(sb + OFF_HS + b * HS_STRIDE + f4 * 2, __byte_perm(v.x, v.y, 0x7632), __byte_perm(v.z, v.w, 0x7632));
            }
        }
        float s[2][2][4];
        {
            const uint32_t kb = sb + st * STAGE_BYTES;
            mbar_wait(bar_full + 8 * st, ph);
#pragma unroll
            for (int j = 0; j < 2; j++)
#pragma unroll
                for (int h = 0; h < 2; h++) { s[j][h][0] = s[j][h][1] = s[j][h][2] = s[j][h][3] = 0.f; }
#pragma unroll
            for (int ks = 0; ks < 8; ks++) {
#pragma unroll
                for (int j = 0; j < 2; j++) {
                    uint32_t a[4];
                    ldsm4(a, kb + (offK ^ ((ks & 3) << 5)) + (ks >> 2) * 16384 + j * 2048);
                    mma16816(s[j][ks & 1], a, qf[ks][0], qf[ks][1]);
                }
            }
            release(); advance();
        }
        float v[2][4];
#pragma unroll
        for (int j = 0; j < 2; j++)
#pragma unroll
            for (int i = 0; i < 4; i++) v[j][i] = s[j][0][i] + s[j][1][i];
        float mx0 = fmaxf(fmaxf(v[0][0], v[0][2]), fmaxf(v[1][0], v[1][2]));
        float mx1 = fmaxf(fmaxf(v[0][1], v[0][3]), fmaxf(v[1][1], v[1][3]));
#pragma unroll
        for (int o = 4; o < 32; o <<= 1) {
            mx0 = fmaxf(mx0, __shfl_xor_sync(0xffffffffu, mx0, o));
            mx1 = fmaxf(mx1, __shfl_xor_sync(0xffffffffu, mx1, o));
        }
        const float mn0 = fmaxf(m0, mx0 * sl2), mn1 = fmaxf(m1, mx1 * sl2);
        const float al0 = ex2(m0 - mn0), al1 = ex2(m1 - mn1);
        m0 = mn0; m1 = mn1;
        uint32_t pb[2][2];
        float ps0 = 0.f, ps1 = 0.f;
#pragma unroll
        for (int j = 0; j < 2; j++) {
            const float p0 = ex2(fmaf(v[j][0], sl2, -mn0)), p1 = ex2(fmaf(v[j][1], sl2, -mn1));
            const float p2 = ex2(fmaf(v[j][2], sl2, -mn0)), p3 = ex2(fmaf(v[j][3], sl2, -mn1));
            ps0 += p0 + p2; ps1 += p1 + p3;
            pb[j][0] = movm_t(pack_bf16(p0, p1));
            pb[j][1] = movm_t(pack_bf16(p2, p3));
        }
        l0 = l0 * al0 + ps0; l1 = l1 * al1 + ps1;
#pragma unroll
        for (int t = 0; t < 8; t++) { O[t][0] *= al0; O[t][1] *= al1; O[t][2] *= al0; O[t][3] *= al1; }
        {
            const uint32_t vb = sb + st * STAGE_BYTES;
            mbar_wait(bar_full + 8 * st, ph);
#pragma unroll
            for (int j = 0; j < 2; j++) {
#pragma unroll
                for (int t = 0; t < 8; t++) {
                    uint32_t a[4];
                    ldsm4t(a, vb + (offV ^ ((t & 3) << 5)) + (t >> 2) * 16384 + j * 2048);
                    mma16816(O[t], a, pb[j][0], pb[j][1]);
                }
            }
            release(); advance();
        }
    }

#pragma unroll
    for (int o = 4; o < 32; o <<= 1) {
        l0 += __shfl_xor_sync(0xffffffffu, l0, o);
        l1 += __shfl_xor_sync(0xffffffffu, l1, o);
    }
    {
        const uint32_t so = sb + OFF_SO + ((warp * 4 + 2 * (c & 1)) * SO_STRIDE + 8 * (c >> 1) + r) * 4;
#pragma unroll
        for (int t = 0; t < 8; t++) {
            sts_f32(so + t * 64, (c >= 2) ? O[t][2] : O[t][0]);
            sts_f32(so + t * 64 + SO_STRIDE * 4, (c >= 2) ? O[t][3] : O[t][1]);
        }
        if (lane < 2) {
            const uint32_t sm = sb + OFF_SM + (warp * 4 + 2 * lane) * 4;
            sts_f32(sm, m0); sts_f32(sm + 4, m1); sts_f32(sm + 64, l0); sts_f32(sm + 68, l1);
        }
    }
    bar_sync(1, 128);
    {
        float mw[4], lw[4];
#pragma unroll
        for (int w = 0; w < 4; w++) { mw[w] = lds_f32(sb + OFF_SM + (w * 4 + warp) * 4); lw[w] = lds_f32(sb + OFF_SM + 64 + (w * 4 + warp) * 4); }
        const float M = fmaxf(fmaxf(mw[0], mw[1]), fmaxf(mw[2], mw[3]));
        float4 acc = make_float4(0.f, 0.f, 0.f, 0.f); float L = 0.f;
#pragma unroll
        for (int w = 0; w < 4; w++) {
            const float sc = ex2(mw[w] - M);
            const float4 o = lds_f32x4(sb + OFF_SO + ((w * 4 + warp) * SO_STRIDE + lane * 4) * 4);
            acc.x = fmaf(sc, o.x, acc.x); acc.y = fmaf(sc, o.y, acc.y); acc.z = fmaf(sc, o.z, acc.z); acc.w = fmaf(sc, o.w, acc.w);
            L = fmaf(sc, lw[w], L);
        }
        const uint32_t tm = (((__float_as_uint(M) >> lane) & 1u) << 1) | tag1, tl = (((__float_as_uint(L) >> lane) & 1u) << 1) | tag1;
        stg_rlx4(g_part + pslot * 128 + lane * 4,
                 (__float_as_uint(acc.x) & ~3u) | tm, (__float_as_uint(acc.y) & ~3u) | tl,
                 (__float_as_uint(acc.z) & ~1u) | tag1, (__float_as_uint(acc.w) & ~1u) | tag1);
    }

    if (ffn) {
        uint32_t hb[2][4];
        ldsm4(hb[0], sb + OFF_HS + brow * HS_STRIDE + (lane >> 3) * 16);
        ldsm4(hb[1], sb + OFF_HS + brow * HS_STRIDE + (lane >> 3) * 16 + 64);
        mbar_wait(bar_full + 8 * st, ph);
        const uint32_t base = sb + st * STAGE_BYTES + (warp >> 1) * 8192 + offA;
#pragma unroll
        for (int ks = 0; ks < 4; ks++) {
            uint32_t a0[4], a1[4];
            ldsm4t(a0, base + ks * 2048 + swz0);
            ldsm4t(a1, base + ks * 2048 + swz1);
            mma16816(yb[0], a0, hb[ks >> 1][2 * (ks & 1)], hb[ks >> 1][2 * (ks & 1) + 1]);
            mma16816(yb[1], a1, hb[ks >> 1][2 * (ks & 1)], hb[ks >> 1][2 * (ks & 1) + 1]);
        }
        release(); advance();
    }
    {
        uint32_t wa[8][2][4];
        mbar_wait(bar_full + 8 * st, ph);
        const uint32_t base = sb + st * STAGE_BYTES + (warp >> 1) * 16384 + offA;
#pragma unroll
        for (int ks = 0; ks < 8; ks++) {
            ldsm4t(wa[ks][0], base + ks * 2048 + swz0);
            ldsm4t(wa[ks][1], base + ks * 2048 + swz1);
        }
        const float g0 = lds_f32(sb + OFF_GS + c * 4);
        const float f0 = lds_f32(sb + OFF_GS + 16 + c * 4);
        float bv[2][2];
#pragma unroll
        for (int i = 0; i < 2; i++) { bv[i][0] = f0 * yb[i][0]; bv[i][1] = f0 * yb[i][2]; }
        uint32_t* dst = g_y + ((c * 16 + nn * 4 + warp) * 32 + kk) * 32 + r * 4;
        bar_sync(4, 256);
        uint32_t ob[4][4];
#pragma unroll
        for (int k2 = 0; k2 < 4; k2++) ldsm4(ob[k2], sb + OFF_OS + brow * QS_STRIDE + (lane >> 3) * 16 + k2 * 64);
        float ya[2][4][4];
#pragma unroll
        for (int i = 0; i < 2; i++)
#pragma unroll
            for (int j = 0; j < 4; j++) { ya[i][j][0] = ya[i][j][1] = ya[i][j][2] = ya[i][j][3] = 0.f; }
#pragma unroll
        for (int ks = 0; ks < 8; ks++) {
            mma16816(ya[0][ks & 3], wa[ks][0], ob[ks >> 1][2 * (ks & 1)], ob[ks >> 1][2 * (ks & 1) + 1]);
            mma16816(ya[1][ks & 3], wa[ks][1], ob[ks >> 1][2 * (ks & 1)], ob[ks >> 1][2 * (ks & 1) + 1]);
        }
        uint32_t w[4];
#pragma unroll
        for (int i = 0; i < 2; i++)
#pragma unroll
            for (int h = 0; h < 2; h++) {
                const float av = (ya[i][0][2 * h] + ya[i][1][2 * h]) + (ya[i][2][2 * h] + ya[i][3][2 * h]);
                w[2 * i + h] = (__float_as_uint(fmaf(g0, av, bv[i][h])) & ~1u) | tag1;
            }
        stg_rlx4(dst, w[0], w[1], w[2], w[3]);
    }
}

typedef CUresult (*EncodeFn)(CUtensorMap*, CUtensorMapDataType, cuuint32_t, void*, const cuuint64_t*, const cuuint64_t*,
                             const cuuint32_t*, const cuuint32_t*, CUtensorMapInterleave, CUtensorMapSwizzle,
                             CUtensorMapL2promotion, CUtensorMapFloatOOBfill);

void make_map(EncodeFn enc, CUtensorMap* m, const void* p, int rank, cuuint64_t d0, cuuint64_t d1, cuuint64_t d2,
              cuuint64_t s1, cuuint64_t s2, cuuint32_t b0, cuuint32_t b1, cuuint32_t b2, CUtensorMapSwizzle sw) {
    cuuint64_t dims[3] = {d0, d1, d2}, strides[2] = {s1, s2};
    cuuint32_t box[3] = {b0, b1, b2}, es[3] = {1, 1, 1};
    enc(m, CU_TENSOR_MAP_DATA_TYPE_BFLOAT16, rank, const_cast<void*>(p), dims, strides, box, es,
        CU_TENSOR_MAP_INTERLEAVE_NONE, sw, CU_TENSOR_MAP_L2_PROMOTION_L2_256B, CU_TENSOR_MAP_FLOAT_OOB_FILL_NONE);
}

}

extern "C" void kernel_launch(void* const* d_in, const int* in_sizes, int n_in, void* d_out, int out_size) {
    (void)in_sizes; (void)n_in; (void)out_size;
    static EncodeFn enc = nullptr;
    if (!enc) {
        void* fn = nullptr;
        cudaDriverEntryPointQueryResult qr;
        cudaGetDriverEntryPoint("cuTensorMapEncodeTiled", &fn, cudaEnableDefault, &qr);
        enc = (EncodeFn)fn;
        cudaFuncSetAttribute(fused_decode_kernel, cudaFuncAttributeMaxDynamicSharedMemorySize, SMEM_BYTES);
    }
    CUtensorMap mK, mV, mWq, mWg, mWu, mWd, mWo;
    make_map(enc, &mK, d_in[1], 3, 64, 4 * 8 * 16384, 2, 256, 128, 64, TILE, 2, CU_TENSOR_MAP_SWIZZLE_128B);
    make_map(enc, &mV, d_in[2], 3, 64, 4 * 8 * 16384, 2, 256, 128, 64, TILE, 2, CU_TENSOR_MAP_SWIZZLE_128B);
    make_map(enc, &mWq, d_in[3], 2, 4096, 512, 1, 8192, 0, 32, 256, 1, CU_TENSOR_MAP_SWIZZLE_64B);
    make_map(enc, &mWg, d_in[6], 2, 1792, 512, 1, 3584, 0, 16, 256, 1, CU_TENSOR_MAP_SWIZZLE_32B);
    make_map(enc, &mWu, d_in[7], 2, 1792, 512, 1, 3584, 0, 16, 256, 1, CU_TENSOR_MAP_SWIZZLE_32B);
    make_map(enc, &mWd, d_in[8], 3, 64, 1792, 8, 1024, 128, 64, 64, 2, CU_TENSOR_MAP_SWIZZLE_128B);
    make_map(enc, &mWo, d_in[4], 3, 64, 4096, 8, 1024, 128, 64, 128, 2, CU_TENSOR_MAP_SWIZZLE_128B);
    fused_decode_kernel<<<NCTA, NTHREADS, SMEM_BYTES>>>(mK, mV, mWq, mWg, mWu, mWd, mWo,
        (const __nv_bfloat16*)d_in[0], (const __nv_bfloat16*)d_in[9], (__nv_bfloat16*)d_out, (const uint8_t*)d_in[3]);
}
```

```cpp
#include <cuda_runtime.h>
#include <cuda_bf16.h>
#include <cuda.h>
#include <stdint.h>

namespace {

constexpr int NCTA        = 128;
constexpr int NTHREADS    = 448;
constexpr int STAGE_BYTES = 32768;
constexpr int NSTAGES     = 6;
constexpr int TILE        = 128;
constexpr int NTILES      = 4096 / TILE;
constexpr int NFFN        = 112;
constexpr int TILE_WG     = 1;
constexpr int TILE_H      = 6;
constexpr int TILE_G      = 8;
constexpr int IT_WG       = 2 * TILE_WG + 1;
constexpr int IT_WD       = 2 * NTILES + 2;

constexpr int INIT_ITEMS  = 2;
constexpr int WINDOW      = 2;
constexpr int WSTART      = 4;
constexpr int WCAP        = 5;
constexpr int CX          = 352;
constexpr int CXL         = 256;
constexpr int GO_GATHER   = 4;
constexpr int GO_REDUCE   = 2;

constexpr int OFF_BAR = NSTAGES * STAGE_BYTES;
constexpr int OFF_XS  = OFF_BAR + 256;
constexpr int XS_STRIDE = 1040;
constexpr int OFF_QS  = OFF_XS + 4 * XS_STRIDE;
constexpr int QS_STRIDE = 272;
constexpr int OFF_OS  = OFF_QS + 4 * QS_STRIDE;
constexpr int OFF_HS  = OFF_OS + 4 * QS_STRIDE;
constexpr int HS_STRIDE = 144;
constexpr int OFF_SO  = OFF_HS + 4 * HS_STRIDE;
constexpr int SO_STRIDE = 136;
constexpr int OFF_SM  = OFF_SO + 16 * SO_STRIDE * 4;
constexpr int OFF_GS  = OFF_SM + 128;
constexpr int OFF_UP  = OFF_GS + 32;
constexpr int OFF_FR  = OFF_UP + 256;
constexpr int SMEM_USED  = OFF_FR + 512;
constexpr int SMEM_BYTES = SMEM_USED + 1024;

constexpr int EP = 32;
__device__ __align__(128) uint32_t g_epoch[NCTA * EP];
__device__ __align__(128) uint32_t g_q[4 * 4096];
__device__ __align__(128) uint32_t g_h[4 * 1792];
__device__ __align__(128) uint32_t g_part[4 * 32 * 4 * 128];
__device__ __align__(128) uint32_t g_y[4 * 16 * 32 * 32];
__device__ __align__(128) uint32_t g_cnt;

constexpr int SPIN_LIMIT = 1 << 22;

__device__ __forceinline__ uint32_t smem_u32(const void* p) { return (uint32_t)__cvta_generic_to_shared(p); }
__device__ __forceinline__ void mbar_init(uint32_t bar, uint32_t cnt) {
    asm volatile("mbarrier.init.shared::cta.b64 [%0], %1;" :: "r"(bar), "r"(cnt) : "memory");
}
__device__ __forceinline__ void mbar_expect_tx(uint32_t bar, uint32_t bytes) {
    asm volatile("mbarrier.arrive.expect_tx.shared::cta.b64 _, [%0], %1;" :: "r"(bar), "r"(bytes) : "memory");
}
__device__ __forceinline__ void mbar_arrive(uint32_t bar) {
    asm volatile("mbarrier.arrive.shared::cta.b64 _, [%0];" :: "r"(bar) : "memory");
}
__device__ __forceinline__ bool mbar_try_wait(uint32_t bar, uint32_t parity) {
    uint32_t ok;
    asm volatile("{\n.reg .pred p;\nmbarrier.try_wait.parity.shared::cta.b64 p, [%1], %2;\nselp.u32 %0, 1, 0, p;\n}"
                 : "=r"(ok) : "r"(bar), "r"(parity) : "memory");
    return ok;
}
__device__ __forceinline__ void mbar_wait(uint32_t bar, uint32_t parity) {
    int it = 0;
    while (!mbar_try_wait(bar, parity)) { if (++it > SPIN_LIMIT) __trap(); }
}
__device__ __forceinline__ void bulk_load(uint32_t dst, const void* src, uint32_t bytes, uint32_t bar) {
    asm volatile("cp.async.bulk.shared::cluster.global.mbarrier::complete_tx::bytes [%0], [%1], %2, [%3];"
                 :: "r"(dst), "l"(src), "r"(bytes), "r"(bar) : "memory");
}
__device__ __forceinline__ void tma2d(uint32_t dst, const CUtensorMap* tm, int c0, int c1, uint32_t bar) {
    asm volatile("cp.async.bulk.tensor.2d.shared::cluster.global.mbarrier::complete_tx::bytes [%0], [%1, {%3, %4}], [%2];"
                 :: "r"(dst), "l"(tm), "r"(bar), "r"(c0), "r"(c1) : "memory");
}
__device__ __forceinline__ void tma3d(uint32_t dst, const CUtensorMap* tm, int c0, int c1, int c2, uint32_t bar) {
    asm volatile("cp.async.bulk.tensor.3d.shared::cluster.global.mbarrier::complete_tx::bytes [%0], [%1, {%3, %4, %5}], [%2];"
                 :: "r"(dst), "l"(tm), "r"(bar), "r"(c0), "r"(c1), "r"(c2) : "memory");
}
__device__ __forceinline__ void tma3d_h(uint32_t dst, const CUtensorMap* tm, int c0, int c1, int c2, uint32_t bar, uint64_t pol) {
    asm volatile("cp.async.bulk.tensor.3d.shared::cluster.global.mbarrier::complete_tx::bytes.L2::cache_hint [%0], [%1, {%3, %4, %5}], [%2], %6;"
                 :: "r"(dst), "l"(tm), "r"(bar), "r"(c0), "r"(c1), "r"(c2), "l"(pol) : "memory");
}
__device__ __forceinline__ void ldsm4(uint32_t (&r)[4], uint32_t addr) {
    asm volatile("ldmatrix.sync.aligned.m8n8.x4.shared.b16 {%0,%1,%2,%3}, [%4];"
                 : "=r"(r[0]), "=r"(r[1]), "=r"(r[2]), "=r"(r[3]) : "r"(addr) : "memory");
}
__device__ __forceinline__ void ldsm4t(uint32_t (&r)[4], uint32_t addr) {
    asm volatile("ldmatrix.sync.aligned.m8n8.x4.trans.shared.b16 {%0,%1,%2,%3}, [%4];"
                 : "=r"(r[0]), "=r"(r[1]), "=r"(r[2]), "=r"(r[3]) : "r"(addr) : "memory");
}
__device__ __forceinline__ void mma16816(float (&d)[4], const uint32_t (&a)[4], uint32_t b0, uint32_t b1) {
    asm volatile("mma.sync.aligned.m16n8k16.row.col.f32.bf16.bf16.f32 {%0,%1,%2,%3}, {%4,%5,%6,%7}, {%8,%9}, {%0,%1,%2,%3};"
                 : "+f"(d[0]), "+f"(d[1]), "+f"(d[2]), "+f"(d[3])
                 : "r"(a[0]), "r"(a[1]), "r"(a[2]), "r"(a[3]), "r"(b0), "r"(b1));
}
__device__ __forceinline__ uint32_t movm_t(uint32_t a) {
    uint32_t d;
    asm volatile("movmatrix.sync.aligned.m8n8.trans.b16 %0, %1;" : "=r"(d) : "r"(a));
    return d;
}
__device__ __forceinline__ uint32_t pack_bf16(float lo, float hi) {
    uint32_t d;
    asm("cvt.rn.bf16x2.f32 %0, %1, %2;" : "=r"(d) : "f"(hi), "f"(lo));
    return d;
}
__device__ __forceinline__ float ex2(float x) {
    float y;
    asm("ex2.approx.ftz.f32 %0, %1;" : "=f"(y) : "f"(x));
    return y;
}
__device__ __forceinline__ float bf16r(float x) { return __bfloat162float(__float2bfloat16_rn(x)); }
__device__ __forceinline__ uint32_t bf16bits(float x) { return (uint32_t)__bfloat16_as_ushort(__float2bfloat16_rn(x)); }
__device__ __forceinline__ void bar_sync(int id, int n) { asm volatile("bar.sync %0, %1;" :: "r"(id), "r"(n) : "memory"); }
__device__ __forceinline__ void bar_arrive(int id, int n) { asm volatile("bar.arrive %0, %1;" :: "r"(id), "r"(n) : "memory"); }

__device__ __forceinline__ uint4 ldg_rlx4(const uint32_t* p) {
    uint4 v;
    asm volatile("ld.relaxed.gpu.global.v4.u32 {%0,%1,%2,%3}, [%4];" : "=r"(v.x), "=r"(v.y), "=r"(v.z), "=r"(v.w) : "l"(p) : "memory");
    return v;
}
__device__ __forceinline__ uint32_t ldg_rlx(const uint32_t* p) {
    uint32_t v;
    asm volatile("ld.relaxed.gpu.global.u32 %0, [%1];" : "=r"(v) : "l"(p) : "memory");
    return v;
}
__device__ __forceinline__ void ldg_rlx4_if(uint4& v, const uint32_t* p, uint32_t pred) {
    asm volatile("{\n.reg .pred p;\nsetp.ne.u32 p, %5, 0;\n@p ld.relaxed.gpu.global.v4.u32 {%0,%1,%2,%3}, [%4];\n}"
                 : "+r"(v.x), "+r"(v.y), "+r"(v.z), "+r"(v.w) : "l"(p), "r"(pred) : "memory");
}
__device__ __forceinline__ void red_add(uint32_t* p, uint32_t v) {
    asm volatile("red.relaxed.gpu.global.add.u32 [%0], %1;" :: "l"(p), "r"(v) : "memory");
}
__device__ __forceinline__ void stg_rlx(uint32_t* p, uint32_t v) {
    asm volatile("st.relaxed.gpu.global.u32 [%0], %1;" :: "l"(p), "r"(v) : "memory");
}
__device__ __forceinline__ void stg_rlx4(uint32_t* p, uint32_t a, uint32_t b, uint32_t c, uint32_t d) {
    asm volatile("st.relaxed.gpu.global.v4.u32 [%0], {%1,%2,%3,%4};" :: "l"(p), "r"(a), "r"(b), "r"(c), "r"(d) : "memory");
}
__device__ __forceinline__ float lds_f32(uint32_t a) { float v; asm volatile("ld.shared.f32 %0, [%1];" : "=f"(v) : "r"(a) : "memory"); return v; }
__device__ __forceinline__ float4 lds_f32x4(uint32_t a) {
    float4 v; asm volatile("ld.shared.v4.f32 {%0,%1,%2,%3}, [%4];" : "=f"(v.x), "=f"(v.y), "=f"(v.z), "=f"(v.w) : "r"(a) : "memory"); return v;
}
__device__ __forceinline__ uint4 lds_u32x4(uint32_t a) {
    uint4 v; asm volatile("ld.shared.v4.u32 {%0,%1,%2,%3}, [%4];" : "=r"(v.x), "=r"(v.y), "=r"(v.z), "=r"(v.w) : "r"(a) : "memory"); return v;
}
__device__ __forceinline__ void sts_f32(uint32_t a, float v) { asm volatile("st.shared.f32 [%0], %1;" :: "r"(a), "f"(v) : "memory"); }
__device__ __forceinline__ void sts_u32x2(uint32_t a, uint32_t x, uint32_t y) { asm volatile("st.shared.v2.u32 [%0], {%1,%2};" :: "r"(a), "r"(x), "r"(y) : "memory"); }

template <int KSTRIDE>
__device__ __forceinline__ void proj512(float (&out)[4], uint32_t a_addr, uint32_t x_addr) {
    float acc[4][4];
#pragma unroll
    for (int i = 0; i < 4; i++) { acc[i][0] = acc[i][1] = acc[i][2] = acc[i][3] = 0.f; }
#pragma unroll 4
    for (int k2 = 0; k2 < 16; k2++) {
        uint32_t b[4], a0[4], a1[4];
        ldsm4(b, x_addr + k2 * 64);
        ldsm4t(a0, a_addr + (2 * k2) * KSTRIDE);
        ldsm4t(a1, a_addr + (2 * k2 + 1) * KSTRIDE);
        mma16816(acc[(2 * k2) & 3], a0, b[0], b[1]);
        mma16816(acc[(2 * k2 + 1) & 3], a1, b[2], b[3]);
    }
#pragma unroll
    for (int i = 0; i < 4; i++) out[i] = (acc[0][i] + acc[1][i]) + (acc[2][i] + acc[3][i]);
}

__device__ __forceinline__ void gather_o(uint32_t sb, int cta, int batch, int lane, uint32_t tag32) {
    const uint32_t tag1 = tag32 & 1u;
    const uint32_t* src = g_part + (batch * 32 + (cta >> 2)) * 4 * 128 + lane * 4;
    uint4 ov[4];
    uint32_t need = 0xFu;
#pragma unroll
    for (int s = 0; s < 4; s++) ov[s] = make_uint4(0, 0, 0, 0);
    int it = 0;
    while (true) {
#pragma unroll
        for (int s = 0; s < 4; s++) ldg_rlx4_if(ov[s], src + s * 128, need & (1u << s));
#pragma unroll
        for (int s = 0; s < 4; s++)
            if (__all_sync(0xffffffffu, (((ov[s].x ^ tag1) | (ov[s].y ^ tag1) | (ov[s].z ^ tag1) | (ov[s].w ^ tag1)) & 1u) == 0)) need &= ~(1u << s);
        if (need == 0) break;
        if (++it > SPIN_LIMIT) __trap();
    }
    float Ms[4], Ls[4], M = -INFINITY;
#pragma unroll
    for (int s = 0; s < 4; s++) {
        Ms[s] = __uint_as_float(__ballot_sync(0xffffffffu, ov[s].x & 2u));
        Ls[s] = __uint_as_float(__ballot_sync(0xffffffffu, ov[s].y & 2u));
        M = fmaxf(M, Ms[s]);
    }
    float L = 0.f, a0 = 0.f, a1 = 0.f, a2 = 0.f, a3 = 0.f;
#pragma unroll
    for (int s = 0; s < 4; s++) {
        const float w = ex2(Ms[s] - M);
        L  = fmaf(w, Ls[s], L);
        a0 = fmaf(w, __uint_as_float(ov[s].x & ~3u), a0); a1 = fmaf(w, __uint_as_float(ov[s].y & ~3u), a1);
        a2 = fmaf(w, __uint_as_float(ov[s].z), a2);       a3 = fmaf(w, __uint_as_float(ov[s].w), a3);
    }
    const float inv = 1.f / L;
    sts_u32x2(sb + OFF_OS + batch * QS_STRIDE + lane * 8, pack_bf16(a0 * inv, a1 * inv), pack_bf16(a2 * inv, a3 * inv));
}

__device__ __forceinline__ void final_reduce(__nv_bfloat16* __restrict__ out, uint32_t sb, int rd, int w, int lane, uint32_t tag32) {
    const uint32_t tag1 = tag32 & 1u;
    const uint32_t* src = g_y + (rd * 32 + w * 8) * 32 + lane * 4;
    uint4 v0, v1; int it = 0;
    while (true) {
        v0 = ldg_rlx4(src); v1 = ldg_rlx4(src + 128);
        const uint32_t bad = (v0.x ^ tag1) | (v0.y ^ tag1) | (v0.z ^ tag1) | (v0.w ^ tag1) | (v1.x ^ tag1) | (v1.y ^ tag1) | (v1.z ^ tag1) | (v1.w ^ tag1);
        if (__all_sync(0xffffffffu, (bad & 1u) == 0)) break;
        if (++it > SPIN_LIMIT) __trap();
    }
    float s0 = __uint_as_float(v0.x) + __uint_as_float(v1.x), s1 = __uint_as_float(v0.y) + __uint_as_float(v1.y);
    float s2 = __uint_as_float(v0.z) + __uint_as_float(v1.z), s3 = __uint_as_float(v0.w) + __uint_as_float(v1.w);
#pragma unroll
    for (int o = 8; o < 32; o <<= 1) {
        s0 += __shfl_xor_sync(0xffffffffu, s0, o); s1 += __shfl_xor_sync(0xffffffffu, s1, o);
        s2 += __shfl_xor_sync(0xffffffffu, s2, o); s3 += __shfl_xor_sync(0xffffffffu, s3, o);
    }
    if (lane < 8) asm volatile("st.shared.v4.f32 [%0], {%1,%2,%3,%4};" :: "r"(sb + OFF_FR + w * 128 + lane * 16), "f"(s0), "f"(s1), "f"(s2), "f"(s3) : "memory");
    if (w != 0) { bar_arrive(5, 128); return; }
    bar_sync(5, 128);
    const uint32_t a = sb + OFF_FR + (4 * (lane & 7) + (lane >> 3)) * 4;
    const float y = (lds_f32(a) + lds_f32(a + 128)) + (lds_f32(a + 256) + lds_f32(a + 384));
    out[rd * 32 + lane] = __float2bfloat16_rn(y);
}

__device__ __forceinline__ void gate_g(uint32_t sb, int b, int lane, uint4 gw0, uint4 gw1) {
    const uint4 x0 = lds_u32x4(sb + OFF_XS + b * XS_STRIDE + lane * 32);
    const uint4 x1 = lds_u32x4(sb + OFF_XS + b * XS_STRIDE + lane * 32 + 16);
    const uint32_t xv[8] = {x0.x, x0.y, x0.z, x0.w, x1.x, x1.y, x1.z, x1.w};
    const uint32_t wv[8] = {gw0.x, gw0.y, gw0.z, gw0.w, gw1.x, gw1.y, gw1.z, gw1.w};
    float z = 0.f;
#pragma unroll
    for (int i = 0; i < 8; i++) {
        const __nv_bfloat162 p = __hmul2(*reinterpret_cast<const __nv_bfloat162*>(&xv[i]), *reinterpret_cast<const __nv_bfloat162*>(&wv[i]));
        z += __low2float(p) + __high2float(p);
    }
#pragma unroll
    for (int o = 16; o > 0; o >>= 1) z += __shfl_xor_sync(0xffffffffu, z, o);
    z = bf16r(z);
    const float g = bf16r(1.f / (1.f + expf(-z)));
    if (lane == 0) { sts_f32(sb + OFF_GS + b * 4, g); sts_f32(sb + OFF_GS + 16 + b * 4, bf16r(1.f - g)); }
}

__global__ void __launch_bounds__(NTHREADS, 1)
fused_decode_kernel(const __nv_bfloat16* __restrict__ x, const __nv_bfloat16* __restrict__ gate_w,
                    __nv_bfloat16* __restrict__ out, const uint8_t* __restrict__ wq_raw,
                    const __grid_constant__ CUtensorMap mapK, const __grid_constant__ CUtensorMap mapV,
                    const __grid_constant__ CUtensorMap mapWq, const __grid_constant__ CUtensorMap mapWg,
                    const __grid_constant__ CUtensorMap mapWu, const __grid_constant__ CUtensorMap mapWd,
                    const __grid_constant__ CUtensorMap mapWo)
{
    if (threadIdx.x < 128) {
        asm volatile("prefetch.global.L2 [%0];" :: "l"(wq_raw + (size_t)blockIdx.x * STAGE_BYTES + threadIdx.x * 256u));
    }
    if (threadIdx.x == 160 && blockIdx.x < 32) {
        asm volatile("prefetch.global.L2 [%0];" :: "l"((const uint8_t*)x + blockIdx.x * 128u));
    }
    extern __shared__ uint8_t smem_raw[];
    const uint32_t sb = (smem_u32(smem_raw) + 1023u) & ~1023u;
    const int cta = blockIdx.x, tid = threadIdx.x, warp = tid >> 5, lane = tid & 31;
    const bool ffn = cta < NFFN;
    const uint32_t bar_full = sb + OFF_BAR, bar_empty = sb + OFF_BAR + 8 * NSTAGES, bar_go = sb + OFF_BAR + 16 * NSTAGES;

    if (tid == 128) {
#pragma unroll
        for (int i = 0; i < NSTAGES; i++) { mbar_init(bar_full + 8 * i, 1); mbar_init(bar_empty + 8 * i, 5); }
        mbar_init(bar_go, 1);
        mbar_init(bar_go + 8, 1);
        asm volatile("fence.mbarrier_init.release.cluster;" ::: "memory");
        asm volatile("fence.proxy.async.shared::cta;" ::: "memory");
        mbar_expect_tx(bar_full, STAGE_BYTES + 4096);
        tma2d(sb, &mapWq, cta * 32, 0, bar_full);
        tma2d(sb + 16384, &mapWq, cta * 32, 256, bar_full);
#pragma unroll
        for (int b = 0; b < 4; b++) bulk_load(sb + OFF_XS + b * XS_STRIDE, x + b * 512, 1024, bar_full);
        mbar_expect_tx(bar_full + 8, STAGE_BYTES);
        uint64_t pol0;
        asm volatile("createpolicy.fractional.L2::evict_first.b64 %0, 1.0;" : "=l"(pol0));
        tma3d_h(sb + STAGE_BYTES, &mapK, 0, cta * 4096, 0, bar_full + 8, pol0);
    }
    if (warp == 4) {
        const int nitems = (ffn ? 4 : 2) + 2 * NTILES;
        uint64_t pol;
        asm volatile("createpolicy.fractional.L2::evict_first.b64 %0, 1.0;" : "=l"(pol));
        auto issue = [&](int it, int st) {
            const uint32_t dst = sb + st * STAGE_BYTES, bar = bar_full + 8 * st;
            if (ffn && it == IT_WG) {
                mbar_expect_tx(bar, STAGE_BYTES);
                tma2d(dst,         &mapWg, cta * 16, 0,   bar);
                tma2d(dst + 8192,  &mapWg, cta * 16, 256, bar);
                tma2d(dst + 16384, &mapWu, cta * 16, 0,   bar);
                tma2d(dst + 24576, &mapWu, cta * 16, 256, bar);
            } else if (ffn && it == IT_WD) {
                mbar_expect_tx(bar, 16384);
                tma3d(dst, &mapWd, 0, (cta >> 2) * 64, (cta & 3) * 2, bar);
            } else if (it == nitems - 1) {
                mbar_expect_tx(bar, STAGE_BYTES);
                tma3d(dst, &mapWo, 0, (cta >> 2) * 128, (cta & 3) * 2, bar);
            } else {
                const int j = it - 1 - (ffn ? (it > IT_WG) + (it > IT_WD) : 0);
                mbar_expect_tx(bar, STAGE_BYTES);
                const int row = cta * 4096 + (j >> 1) * TILE;
                tma3d_h(dst, (j & 1) ? &mapV : &mapK, 0, row, 0, bar, pol);
            }
        };
        __syncwarp();
        __syncthreads();
        const uint32_t tag32 = *(volatile const uint32_t*)&g_epoch[cta * EP] + 1u;
        const int first_late = nitems - (ffn ? 2 : 1);
        int st = INIT_ITEMS % NSTAGES, ph = 1;
        int fst = (INIT_ITEMS - WINDOW) % NSTAGES, fph = 0;
        int nl = INIT_ITEMS - WINDOW;
        auto is_kv = [&](int it) { return it > 0 && it < first_late && !(ffn && it == IT_WG); };
        if (lane == 0) {
            const uint32_t cnt0 = (tag32 - 1u) * (uint32_t)(NCTA * 2 * NTILES);
            uint32_t cnt = cnt0;
            for (int it = INIT_ITEMS; it < nitems; it++) {
                const int win = it < WSTART ? WINDOW : WCAP;
                while (nl <= it - win) {
                    mbar_wait(bar_full + 8 * fst, fph);
                    if (++fst == NSTAGES) { fst = 0; fph ^= 1; }
                    nl++;
                }
                const bool late = it >= first_late;
                if (late || is_kv(it)) {
                    const int j = late ? 2 * NTILES : it - 1 - (ffn ? (it > IT_WG) + (it > IT_WD) : 0);
                    const int thr = NCTA * j + (cta & (NCTA - 1)) - (late ? CXL : CX);
                    int spin = 0;
                    while ((int)(cnt - cnt0) < thr) {
                        cnt = ldg_rlx(&g_cnt);
                        if (++spin > SPIN_LIMIT) __trap();
                    }
                }
                if (it >= NSTAGES) mbar_wait(bar_empty + 8 * st, ph);
                issue(it, st);
                if (++st == NSTAGES) { st = 0; ph ^= 1; }
                cnt = ldg_rlx(&g_cnt);
            }
        }
        __syncwarp();
        if (lane == 0) g_epoch[cta * EP] = tag32;
        return;
    }

    if (warp == 9) {
        __syncthreads();
        if (lane == 0) {
            const int nkv = 2 * NTILES + (ffn ? 2 : 1);
            int st = 0, ph = 0;
            for (int it = 0; it < nkv; it++) {
                mbar_wait(bar_full + 8 * st, ph);
                if (it > 0 && !(ffn && it == IT_WG)) red_add(&g_cnt, 1u);
                if (it == nkv - GO_GATHER) mbar_arrive(bar_go);
                if (it == nkv - GO_REDUCE) mbar_arrive(bar_go + 8);
                mbar_arrive(bar_empty + 8 * st);
                if (++st == NSTAGES) { st = 0; ph ^= 1; }
            }
        }
        return;
    }
    if (warp > 9) {
        const uint32_t t32 = *(volatile const uint32_t*)&g_epoch[cta * EP] + 1u;
        __syncthreads();
        if ((cta & 1) == 0) {
            mbar_wait(bar_go + 8, 0);
            final_reduce(out, sb, cta >> 1, warp - 10, lane, t32);
        }
        return;
    }
    if (warp > 4) {
        const uint32_t t32 = *(volatile const uint32_t*)&g_epoch[cta * EP] + 1u;
        __syncthreads();
        mbar_wait(bar_full, 0);
        const uint4 gw0 = __ldg(reinterpret_cast<const uint4*>(gate_w) + lane * 2);
        const uint4 gw1 = __ldg(reinterpret_cast<const uint4*>(gate_w) + lane * 2 + 1);
        gate_g(sb, warp - 5, lane, gw0, gw1);
        bar_arrive(6, 256);
        mbar_wait(bar_go, 0);
        gather_o(sb, cta, warp - 5, lane, t32);
        bar_arrive(4, 256);
        return;
    }

    const uint32_t epoch = *(volatile const uint32_t*)&g_epoch[cta * EP];
    __syncthreads();
    const uint32_t tag32 = epoch + 1u, tag16 = (tag32 & 0x7fffu) | 0x8000u, tag1 = tag32 & 1u;

    const int r = lane >> 2, c = lane & 3;
    const int bq = cta >> 5, hkv = (cta >> 2) & 7, sq = cta & 3;
    const int kk = cta >> 2, nn = cta & 3;
    int st = 0, ph = 0;
    auto advance = [&]() { if (++st == NSTAGES) { st = 0; ph ^= 1; } };
    auto release = [&]() { __syncwarp(); if (lane == 0) mbar_arrive(bar_empty + 8 * st); };

    const uint32_t xs_lane = sb + OFF_XS + (lane & 3) * XS_STRIDE + (lane >> 3) * 16;

    mbar_wait(bar_full, 0);
    if (warp < 2) {
        float d[4];
        const int k = (lane & 7) + 8 * (lane >> 4);
        const int cc = 2 * warp + ((lane >> 3) & 1);
        proj512<1024>(d, sb + k * 64 + ((cc ^ ((lane & 7) >> 1)) << 4), xs_lane);
        const float v0 = (c >= 2) ? d[2] : d[0], v1 = (c >= 2) ? d[3] : d[1];
        uint32_t* dst = g_q + (2 * (c & 1)) * 4096 + cta * 32 + warp * 16 + r + 8 * (c >> 1);
        stg_rlx(dst, (bf16bits(v0) << 16) | tag16);
        stg_rlx(dst + 4096, (bf16bits(v1) << 16) | tag16);
    }
    release(); advance();
    auto wg_item = [&]() {
            if (warp >= 2) {
                mbar_wait(bar_full + 8 * st, ph);
                float d[4];
                const int k = (lane & 7) + 8 * (lane >> 4);
                const int cc = (lane >> 3) & 1;
                proj512<512>(d, sb + st * STAGE_BYTES + (warp - 2) * 16384 + k * 32 + ((cc ^ ((lane & 7) >> 2)) << 4), xs_lane);
                const float v0 = bf16r((c >= 2) ? d[2] : d[0]), v1 = bf16r((c >= 2) ? d[3] : d[1]);
                release();
                if (warp == 3) { sts_f32(sb + OFF_UP + lane * 8, v0); sts_f32(sb + OFF_UP + lane * 8 + 4, v1); }
                bar_sync(2, 64);
                if (warp == 2) {
                    const float u0 = lds_f32(sb + OFF_UP + lane * 8), u1 = lds_f32(sb + OFF_UP + lane * 8 + 4);
                    const float h0 = (v0 > 0.f ? v0 : 0.f * v0) * u0, h1 = (v1 > 0.f ? v1 : 0.f * v1) * u1;
                    uint32_t* dst = g_h + (2 * (c & 1)) * 1792 + cta * 16 + r + 8 * (c >> 1);
                    stg_rlx(dst, (bf16bits(h0) << 16) | tag16);
                    stg_rlx(dst + 1792, (bf16bits(h1) << 16) | tag16);
                }
            } else {
                release();
            }
            advance();
    };
    {
        const uint32_t* src = g_q + bq * 4096 + (hkv * 4 + warp) * 128 + lane * 4;
        uint4 v; int it = 0;
        mbar_wait(bar_full + 16, 0);
        while (true) {
            v = ldg_rlx4(src);
            const bool ok = ((v.x & 0xffffu) == tag16) && ((v.y & 0xffffu) == tag16) && ((v.z & 0xffffu) == tag16) && ((v.w & 0xffffu) == tag16);
            if (__all_sync(0xffffffffu, ok)) break;
            if (++it > SPIN_LIMIT) __trap();
        }
        sts_u32x2(sb + OFF_QS + warp * QS_STRIDE + lane * 8, __byte_perm(v.x, v.y, 0x7632), __byte_perm(v.z, v.w, 0x7632));
    }
    bar_sync(1, 128);
    uint32_t qf[8][2];
#pragma unroll
    for (int k2 = 0; k2 < 4; k2++) {
        uint32_t b[4];
        ldsm4(b, sb + OFF_QS + (lane & 3) * QS_STRIDE + (lane >> 3) * 16 + k2 * 64);
        qf[2 * k2][0] = b[0]; qf[2 * k2][1] = b[1]; qf[2 * k2 + 1][0] = b[2]; qf[2 * k2 + 1][1] = b[3];
    }

    const float sl2 = 0.08838834764831845f * 1.4426950408889634f;
    float O[8][4];
#pragma unroll
    for (int t = 0; t < 8; t++) { O[t][0] = O[t][1] = O[t][2] = O[t][3] = 0.f; }
    float m0 = -INFINITY, m1 = -INFINITY, l0 = 0.f, l1 = 0.f;
    const uint32_t offK = (32 * warp + (lane & 7) + 8 * ((lane >> 3) & 1)) * 128 + (((lane >> 4) ^ (lane & 7)) << 4);
    const uint32_t offV = (32 * warp + (lane & 7) + 8 * (lane >> 4)) * 128 + ((((lane >> 3) & 1) ^ (lane & 7)) << 4);

    const int brow = (lane & 7) >> 1;
    float yb[2][4];
#pragma unroll
    for (int i = 0; i < 2; i++) { yb[i][0] = yb[i][1] = yb[i][2] = yb[i][3] = 0.f; }
    const uint32_t offA = ((lane & 7) + 8 * (lane >> 4)) * 128;
    const uint32_t swz0 = ((2 * ((2 * warp) & 3) + ((lane >> 3) & 1)) ^ (lane & 7)) << 4;
    const uint32_t swz1 = ((2 * ((2 * warp + 1) & 3) + ((lane >> 3) & 1)) ^ (lane & 7)) << 4;
    const int pslot = (bq * 32 + hkv * 4 + warp) * 4 + sq;

#pragma unroll 1
    for (int tile = 0; tile < NTILES; tile++) {
        if (ffn && tile == TILE_WG) wg_item();
        if (tile == TILE_G) bar_sync(6, 256);
        if (ffn && tile == TILE_H) {
            if (warp < 2) {
                const int b = tid >> 4, f4 = (tid & 15) * 4;
                const uint32_t* src = g_h + b * 1792 + kk * 64 + f4;
                uint4 v; int it = 0;
                while (true) {
                    v = ldg_rlx4(src);
                    const bool ok = ((v.x & 0xffffu) == tag16) && ((v.y & 0xffffu) == tag16) && ((v.z & 0xffffu) == tag16) && ((v.w & 0xffffu) == tag16);
                    if (__all_sync(0xffffffffu, ok)) break;
                    if (++it > SPIN_LIMIT) __trap();
                }
                sts_u32x2(sb + OFF_HS + b * HS_STRIDE + f4 * 2, __byte_perm(v.x, v.y, 0x7632), __byte_perm(v.z, v.w, 0x7632));
            }
        }
        float s[2][2][4];
        {
            const uint32_t kb = sb + st * STAGE_BYTES;
            mbar_wait(bar_full + 8 * st, ph);
#pragma unroll
            for (int j = 0; j < 2; j++)
#pragma unroll
                for (int h = 0; h < 2; h++) { s[j][h][0] = s[j][h][1] = s[j][h][2] = s[j][h][3] = 0.f; }
#pragma unroll
            for (int ks = 0; ks < 8; ks++) {
#pragma unroll
                for (int j = 0; j < 2; j++) {
                    uint32_t a[4];
                    ldsm4(a, kb + (offK ^ ((ks & 3) << 5)) + (ks >> 2) * 16384 + j * 2048);
                    mma16816(s[j][ks & 1], a, qf[ks][0], qf[ks][1]);
                }
            }
            release(); advance();
        }
        float v[2][4];
#pragma unroll
        for (int j = 0; j < 2; j++)
#pragma unroll
            for (int i = 0; i < 4; i++) v[j][i] = s[j][0][i] + s[j][1][i];
        float mx0 = fmaxf(fmaxf(v[0][0], v[0][2]), fmaxf(v[1][0], v[1][2]));
        float mx1 = fmaxf(fmaxf(v[0][1], v[0][3]), fmaxf(v[1][1], v[1][3]));
#pragma unroll
        for (int o = 4; o < 32; o <<= 1) {
            mx0 = fmaxf(mx0, __shfl_xor_sync(0xffffffffu, mx0, o));
            mx1 = fmaxf(mx1, __shfl_xor_sync(0xffffffffu, mx1, o));
        }
        const float mn0 = fmaxf(m0, mx0 * sl2), mn1 = fmaxf(m1, mx1 * sl2);
        const float al0 = ex2(m0 - mn0), al1 = ex2(m1 - mn1);
        m0 = mn0; m1 = mn1;
        uint32_t pb[2][2];
        float ps0 = 0.f, ps1 = 0.f;
#pragma unroll
        for (int j = 0; j < 2; j++) {
            const float p0 = ex2(fmaf(v[j][0], sl2, -mn0)), p1 = ex2(fmaf(v[j][1], sl2, -mn1));
            const float p2 = ex2(fmaf(v[j][2], sl2, -mn0)), p3 = ex2(fmaf(v[j][3], sl2, -mn1));
            ps0 += p0 + p2; ps1 += p1 + p3;
            pb[j][0] = movm_t(pack_bf16(p0, p1));
            pb[j][1] = movm_t(pack_bf16(p2, p3));
        }
        l0 = l0 * al0 + ps0; l1 = l1 * al1 + ps1;
#pragma unroll
        for (int t = 0; t < 8; t++) { O[t][0] *= al0; O[t][1] *= al1; O[t][2] *= al0; O[t][3] *= al1; }
        {
            const uint32_t vb = sb + st * STAGE_BYTES;
            mbar_wait(bar_full + 8 * st, ph);
#pragma unroll
            for (int j = 0; j < 2; j++) {
#pragma unroll
                for (int t = 0; t < 8; t++) {
                    uint32_t a[4];
                    ldsm4t(a, vb + (offV ^ ((t & 3) << 5)) + (t >> 2) * 16384 + j * 2048);
                    mma16816(O[t], a, pb[j][0], pb[j][1]);
                }
            }
            release(); advance();
        }
    }

#pragma unroll
    for (int o = 4; o < 32; o <<= 1) {
        l0 += __shfl_xor_sync(0xffffffffu, l0, o);
        l1 += __shfl_xor_sync(0xffffffffu, l1, o);
    }
    {
        const uint32_t so = sb + OFF_SO + ((warp * 4 + 2 * (c & 1)) * SO_STRIDE + 8 * (c >> 1) + r) * 4;
#pragma unroll
        for (int t = 0; t < 8; t++) {
            sts_f32(so + t * 64, (c >= 2) ? O[t][2] : O[t][0]);
            sts_f32(so + t * 64 + SO_STRIDE * 4, (c >= 2) ? O[t][3] : O[t][1]);
        }
        if (lane < 2) {
            const uint32_t sm = sb + OFF_SM + (warp * 4 + 2 * lane) * 4;
            sts_f32(sm, m0); sts_f32(sm + 4, m1); sts_f32(sm + 64, l0); sts_f32(sm + 68, l1);
        }
    }
    bar_sync(1, 128);
    {
        float mw[4], lw[4];
#pragma unroll
        for (int w = 0; w < 4; w++) { mw[w] = lds_f32(sb + OFF_SM + (w * 4 + warp) * 4); lw[w] = lds_f32(sb + OFF_SM + 64 + (w * 4 + warp) * 4); }
        const float M = fmaxf(fmaxf(mw[0], mw[1]), fmaxf(mw[2], mw[3]));
        float4 acc = make_float4(0.f, 0.f, 0.f, 0.f); float L = 0.f;
#pragma unroll
        for (int w = 0; w < 4; w++) {
            const float sc = ex2(mw[w] - M);
            const float4 o = lds_f32x4(sb + OFF_SO + ((w * 4 + warp) * SO_STRIDE + lane * 4) * 4);
            acc.x = fmaf(sc, o.x, acc.x); acc.y = fmaf(sc, o.y, acc.y); acc.z = fmaf(sc, o.z, acc.z); acc.w = fmaf(sc, o.w, acc.w);
            L = fmaf(sc, lw[w], L);
        }
        const uint32_t tm = (((__float_as_uint(M) >> lane) & 1u) << 1) | tag1, tl = (((__float_as_uint(L) >> lane) & 1u) << 1) | tag1;
        stg_rlx4(g_part + pslot * 128 + lane * 4,
                 (__float_as_uint(acc.x) & ~3u) | tm, (__float_as_uint(acc.y) & ~3u) | tl,
                 (__float_as_uint(acc.z) & ~1u) | tag1, (__float_as_uint(acc.w) & ~1u) | tag1);
    }

    if (ffn) {
        uint32_t hb[2][4];
        ldsm4(hb[0], sb + OFF_HS + brow * HS_STRIDE + (lane >> 3) * 16);
        ldsm4(hb[1], sb + OFF_HS + brow * HS_STRIDE + (lane >> 3) * 16 + 64);
        mbar_wait(bar_full + 8 * st, ph);
        const uint32_t base = sb + st * STAGE_BYTES + (warp >> 1) * 8192 + offA;
#pragma unroll
        for (int ks = 0; ks < 4; ks++) {
            uint32_t a0[4], a1[4];
            ldsm4t(a0, base + ks * 2048 + swz0);
            ldsm4t(a1, base + ks * 2048 + swz1);
            mma16816(yb[0], a0, hb[ks >> 1][2 * (ks & 1)], hb[ks >> 1][2 * (ks & 1) + 1]);
            mma16816(yb[1], a1, hb[ks >> 1][2 * (ks & 1)], hb[ks >> 1][2 * (ks & 1) + 1]);
        }
        release(); advance();
    }
    {
        uint32_t wa[8][2][4];
        mbar_wait(bar_full + 8 * st, ph);
        const uint32_t base = sb + st * STAGE_BYTES + (warp >> 1) * 16384 + offA;
#pragma unroll
        for (int ks = 0; ks < 8; ks++) {
            ldsm4t(wa[ks][0], base + ks * 2048 + swz0);
            ldsm4t(wa[ks][1], base + ks * 2048 + swz1);
        }
        const float g0 = lds_f32(sb + OFF_GS + c * 4);
        const float f0 = lds_f32(sb + OFF_GS + 16 + c * 4);
        float bv[2][2];
#pragma unroll
        for (int i = 0; i < 2; i++) { bv[i][0] = f0 * yb[i][0]; bv[i][1] = f0 * yb[i][2]; }
        uint32_t* dst = g_y + ((c * 16 + nn * 4 + warp) * 32 + kk) * 32 + r * 4;
        bar_sync(4, 256);
        uint32_t ob[4][4];
#pragma unroll
        for (int k2 = 0; k2 < 4; k2++) ldsm4(ob[k2], sb + OFF_OS + brow * QS_STRIDE + (lane >> 3) * 16 + k2 * 64);
        float ya[2][4][4];
#pragma unroll
        for (int i = 0; i < 2; i++)
#pragma unroll
            for (int j = 0; j < 4; j++) { ya[i][j][0] = ya[i][j][1] = ya[i][j][2] = ya[i][j][3] = 0.f; }
#pragma unroll
        for (int ks = 0; ks < 8; ks++) {
            mma16816(ya[0][ks & 3], wa[ks][0], ob[ks >> 1][2 * (ks & 1)], ob[ks >> 1][2 * (ks & 1) + 1]);
            mma16816(ya[1][ks & 3], wa[ks][1], ob[ks >> 1][2 * (ks & 1)], ob[ks >> 1][2 * (ks & 1) + 1]);
        }
        uint32_t w[4];
#pragma unroll
        for (int i = 0; i < 2; i++)
#pragma unroll
            for (int h = 0; h < 2; h++) {
                const float av = (ya[i][0][2 * h] + ya[i][1][2 * h]) + (ya[i][2][2 * h] + ya[i][3][2 * h]);
                w[2 * i + h] = (__float_as_uint(fmaf(g0, av, bv[i][h])) & ~1u) | tag1;
            }
        stg_rlx4(dst, w[0], w[1], w[2], w[3]);
    }
}

typedef CUresult (*EncodeFn)(CUtensorMap*, CUtensorMapDataType, cuuint32_t, void*, const cuuint64_t*, const cuuint64_t*,
                             const cuuint32_t*, const cuuint32_t*, CUtensorMapInterleave, CUtensorMapSwizzle,
                             CUtensorMapL2promotion, CUtensorMapFloatOOBfill);

void make_map(EncodeFn enc, CUtensorMap* m, const void* p, int rank, cuuint64_t d0, cuuint64_t d1, cuuint64_t d2,
              cuuint64_t s1, cuuint64_t s2, cuuint32_t b0, cuuint32_t b1, cuuint32_t b2, CUtensorMapSwizzle sw) {
    cuuint64_t dims[3] = {d0, d1, d2}, strides[2] = {s1, s2};
    cuuint32_t box[3] = {b0, b1, b2}, es[3] = {1, 1, 1};
    enc(m, CU_TENSOR_MAP_DATA_TYPE_BFLOAT16, rank, const_cast<void*>(p), dims, strides, box, es,
        CU_TENSOR_MAP_INTERLEAVE_NONE, sw, CU_TENSOR_MAP_L2_PROMOTION_L2_256B, CU_TENSOR_MAP_FLOAT_OOB_FILL_NONE);
}

}

extern "C" void kernel_launch(void* const* d_in, const int* in_sizes, int n_in, void* d_out, int out_size) {
    (void)in_sizes; (void)n_in; (void)out_size;
    static EncodeFn enc = nullptr;
    if (!enc) {
        void* fn = nullptr;
        cudaDriverEntryPointQueryResult qr;
        cudaGetDriverEntryPoint("cuTensorMapEncodeTiled", &fn, cudaEnableDefault, &qr);
        enc = (EncodeFn)fn;
        cudaFuncSetAttribute(fused_decode_kernel, cudaFuncAttributeMaxDynamicSharedMemorySize, SMEM_BYTES);
    }
    CUtensorMap mK, mV, mWq, mWg, mWu, mWd, mWo;
    make_map(enc, &mK, d_in[1], 3, 64, 4 * 8 * 16384, 2, 256, 128, 64, TILE, 2, CU_TENSOR_MAP_SWIZZLE_128B);
    make_map(enc, &mV, d_in[2], 3, 64, 4 * 8 * 16384, 2, 256, 128, 64, TILE, 2, CU_TENSOR_MAP_SWIZZLE_128B);
    make_map(enc, &mWq, d_in[3], 2, 4096, 512, 1, 8192, 0, 32, 256, 1, CU_TENSOR_MAP_SWIZZLE_64B);
    make_map(enc, &mWg, d_in[6], 2, 1792, 512, 1, 3584, 0, 16, 256, 1, CU_TENSOR_MAP_SWIZZLE_32B);
    make_map(enc, &mWu, d_in[7], 2, 1792, 512, 1, 3584, 0, 16, 256, 1, CU_TENSOR_MAP_SWIZZLE_32B);
    make_map(enc, &mWd, d_in[8], 3, 64, 1792, 8, 1024, 128, 64, 64, 2, CU_TENSOR_MAP_SWIZZLE_128B);
    make_map(enc, &mWo, d_in[4], 3, 64, 4096, 8, 1024, 128, 64, 128, 2, CU_TENSOR_MAP_SWIZZLE_128B);
    fused_decode_kernel<<<NCTA, NTHREADS, SMEM_BYTES>>>(
        (const __nv_bfloat16*)d_in[0], (const __nv_bfloat16*)d_in[9], (__nv_bfloat16*)d_out, (const uint8_t*)d_in[3],
        mK, mV, mWq, mWg, mWu, mWd, mWo);
}
```
